```python
import torch

def _softmax(x, axis=-1):
    return torch.softmax(x, dim=axis)
def _gelu(x):
    return torch.nn.functional.gelu(x, approximate="tanh")
def _silu(x):
    return torch.nn.functional.silu(x)
def _sigmoid(x):
    return torch.sigmoid(x)
def _layernorm(x, axis=-1, eps=1e-5):
    m = x.mean(dim=axis, keepdim=True)
    v = x.var(dim=axis, keepdim=True, unbiased=False)
    return (x - m) / torch.sqrt(v + eps)
def _scatter_add(tgt, idx, src, axis=0):
    return tgt.clone().index_add_(axis, idx, src)
def _segment_sum(src, seg, n):
    out = torch.zeros((n,) + src.shape[1:], dtype=src.dtype)
    return out.index_add_(0, seg, src)
def _pad(x, pw):
    flat = tuple(v for pair in reversed(pw) for v in pair)
    return torch.nn.functional.pad(x, flat)

kernel_name = 'gated_mix__mha_block__dense_activation_squared_relu__prompt'

def setup_inputs():

    _w = (lambda a: (lambda t: t.to(torch.bfloat16) if t.is_floating_point() else t)(torch.as_tensor(a)))
    def _A_setup():
        B, S, D, H = 1, 2048, 512, 32
        return {
            "x": _w((lambda *s: torch.randn(*s, dtype=torch.bfloat16) * 0.05)(B, S, D)),
            "wqkv": _w((lambda *s: torch.randn(*s, dtype=torch.bfloat16) * 0.8)(D, 3 * D)),
            "wo": _w((lambda *s: torch.randn(*s, dtype=torch.bfloat16) * 0.1)(D, D)),
        }
    _A_in = _A_setup()

    def _B_setup():
        B, S, D, F = 1, 2048, 512, 1376
        return {
            "x": _w((lambda *s: torch.randn(*s, dtype=torch.bfloat16) * 0.05)(B, S, D)),
            "w1": _w((lambda *s: torch.randn(*s, dtype=torch.bfloat16) * 0.1)(D, F)),
            "b1": _w((lambda *s: torch.randn(*s, dtype=torch.bfloat16) * 0.1)(F)),
            "w2": _w((lambda *s: torch.randn(*s, dtype=torch.bfloat16) * 0.1)(F, D)),
            "b2": _w((lambda *s: torch.randn(*s, dtype=torch.bfloat16) * 0.05)(D)),
        }
    _B_in = _B_setup()

    return {
        "A_x": _A_in["x"],
        "A_wqkv": _A_in["wqkv"],
        "A_wo": _A_in["wo"],
        "B_x": _B_in["x"],
        "B_w1": _B_in["w1"],
        "B_b1": _B_in["b1"],
        "B_w2": _B_in["w2"],
        "B_b2": _B_in["b2"],
        "gate_w": _w((lambda *s: torch.randn(*s, dtype=torch.bfloat16) * 0.05)(512) * 16.0),
    }

def reference(A_x, A_wqkv, A_wo, B_x, B_w1, B_b1, B_w2, B_b2, gate_w):
    def _A_ref(x, wqkv, wo):
        B, S, D = x.shape
        H = 32
        Dh = D // H
        qkv = (lambda x, *d: x.permute(*d))((x @ wqkv).reshape(B, S, 3, H, Dh), 2, 0, 3, 1, 4)
        q, k, v = qkv[0], qkv[1], qkv[2]
        scores = torch.einsum("bhqd,bhkd->bhqk", q, k) * (Dh ** -0.5)
        p = _softmax(scores, axis=-1)
        o = torch.einsum("bhqk,bhkd->bhqd", p, v)
        return (lambda x, *d: x.permute(*d))(o, 0, 2, 1, 3).reshape(B, S, D) @ wo

    def _B_ref(x, w1, b1, w2, b2):
        h = torch.einsum("bsd,df->bsf", x, w1) + b1
        zero = torch.zeros_like(h)
        r = torch.where(h > zero, h, zero)
        h = r * r
        out = torch.einsum("bsf,fd->bsd", h, w2) + b2
        return out

    x = A_x
    g = _sigmoid((x * gate_w).sum(-1, keepdims=True))
    a = _A_ref(x, A_wqkv, A_wo)
    b = _B_ref(x, B_w1, B_b1, B_w2, B_b2)
    return g * a + (1 - g) * b
```

```cpp
#include <cuda_runtime.h>
#include <cuda_bf16.h>
#include <cuda_fp16.h>
#include <cuda.h>
#include <stdint.h>

namespace {

constexpr int kS = 2048, kD = 512, kF = 1376;

__device__ __align__(128) uint4 g_Q[32 * 128 * 32];
__device__ __align__(128) uint4 g_KV[32 * 8 * 1024];
__device__ __align__(128) float g_nrm[32 * 2 * 128];
__device__ __align__(128) uint4 g_H[32 * 172 * 64];
__device__ __align__(128) uint4 g_O[32 * 64 * 64];
__device__ __align__(128) float g_gate[kS];
__device__ __align__(128) __nv_bfloat16 g_fb[32 * kS * 32];
__device__ __align__(128) unsigned g_cnt[(1 + 8 + 32 + 64) * 32];
constexpr int CNT_TICKET = 0, CNT_QKV = 1, CNT_H = 9, CNT_O = 41;
#define TLS(i)

constexpr uint32_t SM_RING = 131072;
constexpr uint32_t SLOT = 24576;
constexpr uint32_t SM_ONES = SM_RING;
constexpr uint32_t SM_Q = SM_RING + 4096;
constexpr uint32_t SM_NRM = SM_RING + 20480;
constexpr uint32_t SM_GATE = SM_RING + 22528;
constexpr uint32_t SM_BAR = SM_RING + 4 * SLOT;
constexpr uint32_t B_XFULL = SM_BAR, B_WFULL = B_XFULL + 64, B_WEMPTY = B_WFULL + 32, B_KVFULL = B_WEMPTY + 32,
                   B_KVEMPTY = B_KVFULL + 64, B_AUX = B_KVEMPTY + 64, B_GATE = B_AUX + 8, B_FFULL = B_GATE + 8,
                   B_TAILB = B_FFULL + 24, B_TAILA = B_TAILB + 8, SM_EPOCH = B_TAILA + 32;
constexpr uint32_t SMEM_BYTES = SM_BAR + 512;
constexpr uint32_t XREG = 0x07412653u;

constexpr float kQScale = 0.25f * 1.4426950408889634f;
constexpr float kLam = 1.0f / 128.0f;
constexpr float kPScale = 7.578125f;
constexpr uint32_t kPScaleH2 = 0x47944794u;
__host__ __device__ constexpr bool grp_is_mufu(int grp) { return ((0xA4 >> (grp & 7)) & 1) != 0; }

__device__ __forceinline__ void wg_fence() { asm volatile("wgmma.fence.sync.aligned;" ::: "memory"); }
__device__ __forceinline__ void wg_commit() { asm volatile("wgmma.commit_group.sync.aligned;" ::: "memory"); }
template <int N> __device__ __forceinline__ void wg_wait() { asm volatile("wgmma.wait_group.sync.aligned %0;" ::"n"(N) : "memory"); }
__device__ __forceinline__ uint64_t mkdesc(uint32_t addr, uint32_t lbo, uint32_t sbo, uint32_t swz) {
    return (uint64_t)((addr & 0x3FFFF) >> 4) | ((uint64_t)(lbo >> 4) << 16) | ((uint64_t)(sbo >> 4) << 32) | ((uint64_t)swz << 62);
}
__device__ __forceinline__ void mbar_init(uint32_t a, uint32_t c) { asm volatile("mbarrier.init.shared::cta.b64 [%0], %1;" ::"r"(a), "r"(c) : "memory"); }
__device__ __forceinline__ void mbar_expect(uint32_t a, uint32_t b) { asm volatile("mbarrier.arrive.expect_tx.shared::cta.b64 _, [%0], %1;" ::"r"(a), "r"(b) : "memory"); }
__device__ __forceinline__ void mbar_arrive(uint32_t a) { asm volatile("mbarrier.arrive.shared::cta.b64 _, [%0];" ::"r"(a) : "memory"); }
__device__ __forceinline__ void mbar_arrive_rank(uint32_t a, uint32_t rank) {
    asm volatile("{\n.reg .b32 r;\nmapa.shared::cluster.u32 r, %0, %1;\nmbarrier.arrive.shared::cluster.b64 _, [r];\n}" ::"r"(a), "r"(rank) : "memory");
}
__device__ __forceinline__ bool mbar_test(uint32_t a, uint32_t par) {
    uint32_t ok;
    asm volatile("{\n.reg .pred p;\nmbarrier.test_wait.parity.shared::cta.b64 p, [%1], %2;\nselp.u32 %0, 1, 0, p;\n}" : "=r"(ok) : "r"(a), "r"(par) : "memory");
    return ok != 0;
}
__device__ __forceinline__ void mbar_wait(uint32_t a, uint32_t par) {
    asm volatile(
        "{\n.reg .pred p;\n.reg .u32 n;\nmov.u32 n, 0;\n"
        "L_%=:\n"
        "mbarrier.try_wait.parity.shared::cta.b64 p, [%0], %1;\n"
        "@p bra D_%=;\n"
        "add.u32 n, n, 1;\n"
        "setp.lt.u32 p, n, 0x4000000;\n"
        "@p bra L_%=;\n"
        "trap;\n"
        "D_%=:\n}" ::"r"(a), "r"(par) : "memory");
}
__device__ __forceinline__ void bulk_g2s(uint32_t dst, const void* src, uint32_t bytes, uint32_t bar) {
    asm volatile("cp.async.bulk.shared::cluster.global.mbarrier::complete_tx::bytes [%0], [%1], %2, [%3];" ::"r"(dst), "l"(src), "r"(bytes), "r"(bar) : "memory");
}
__device__ __forceinline__ void tma2d(uint32_t dst, const CUtensorMap* tm, int c0, int c1, uint32_t bar) {
    asm volatile("cp.async.bulk.tensor.2d.shared::cluster.global.mbarrier::complete_tx::bytes [%0], [%1, {%3, %4}], [%2];" ::"r"(dst), "l"(tm), "r"(bar), "r"(c0), "r"(c1) : "memory");
}
__device__ __forceinline__ void tma2d_mc(uint32_t dst, const CUtensorMap* tm, int c0, int c1, uint32_t bar) {
    asm volatile("cp.async.bulk.tensor.2d.shared::cluster.global.mbarrier::complete_tx::bytes.multicast::cluster [%0], [%1, {%3, %4}], [%2], %5;" ::"r"(dst), "l"(tm), "r"(bar), "r"(c0), "r"(c1), "h"((uint16_t)3) : "memory");
}
__device__ __forceinline__ void tma2d_store(const CUtensorMap* tm, uint32_t src, int c0, int c1) {
    asm volatile("cp.async.bulk.tensor.2d.global.shared::cta.bulk_group [%0, {%2, %3}], [%1];" ::"l"(tm), "r"(src), "r"(c0), "r"(c1) : "memory");
}
__device__ __forceinline__ void l2_prefetch(const void* p, uint32_t bytes) { asm volatile("cp.async.bulk.prefetch.L2.global [%0], %1;" ::"l"(p), "r"(bytes) : "memory"); }
__device__ __forceinline__ void fence_async() { asm volatile("fence.proxy.async;" ::: "memory"); }
__device__ __forceinline__ void bar_sync(int id, int n) { asm volatile("bar.sync %0, %1;" ::"r"(id), "r"(n) : "memory"); }
__device__ __forceinline__ void bar_arrive(int id, int n) { asm volatile("bar.arrive %0, %1;" ::"r"(id), "r"(n) : "memory"); }
__device__ __forceinline__ bool bar_or(int id, int n, bool v) {
    uint32_t r;
    asm volatile("{\n.reg .pred p, q;\nsetp.ne.u32 p, %3, 0;\nbar.red.or.pred q, %1, %2, p;\nselp.u32 %0, 1, 0, q;\n}" : "=r"(r) : "r"(id), "r"(n), "r"((uint32_t)v) : "memory");
    return r != 0;
}
__device__ __forceinline__ void cnt_signal(int idx) { asm volatile("red.release.gpu.global.add.u32 [%0], 1;" ::"l"(g_cnt + idx * 32) : "memory"); }
__device__ __forceinline__ bool cnt_test(int idx, unsigned target) {
    unsigned v;
    asm volatile("ld.acquire.gpu.global.u32 %0, [%1];" : "=r"(v) : "l"(g_cnt + idx * 32) : "memory");
    return (int)(v - target) >= 0;
}
__device__ __forceinline__ void cnt_wait(int idx, unsigned target) {
    for (int n = 0; !cnt_test(idx, target); n++) { if (n > (1 << 23)) __trap(); }
}
__device__ __forceinline__ uint32_t pack_h2(float lo, float hi) { uint32_t r; asm("cvt.rn.f16x2.f32 %0, %1, %2;" : "=r"(r) : "f"(hi), "f"(lo)); return r; }
__device__ __forceinline__ uint32_t pack_bf2(float lo, float hi) { uint32_t r; asm("cvt.rn.bf16x2.f32 %0, %1, %2;" : "=r"(r) : "f"(hi), "f"(lo)); return r; }
__device__ __forceinline__ float h_lo(uint32_t v) { return __low2float(*reinterpret_cast<__half2*>(&v)); }
__device__ __forceinline__ float h_hi(uint32_t v) { return __high2float(*reinterpret_cast<__half2*>(&v)); }
__device__ __forceinline__ float bf_lo(uint32_t v) { return __uint_as_float(v << 16); }
__device__ __forceinline__ float bf_hi(uint32_t v) { return __uint_as_float(v & 0xffff0000u); }
__device__ __forceinline__ float bf_round(float v) { return __bfloat162float(__float2bfloat16_rn(v)); }
__device__ __forceinline__ float warp_max_nonneg(float v) { return __uint_as_float(__reduce_max_sync(0xffffffffu, __float_as_uint(v))); }
__device__ __forceinline__ uint32_t hfma2(uint32_t a, uint32_t b, uint32_t c) { uint32_t d; asm("fma.rn.f16x2 %0, %1, %2, %3;" : "=r"(d) : "r"(a), "r"(b), "r"(c)); return d; }
__device__ __forceinline__ uint32_t hfma2_relu(uint32_t a, uint32_t b, uint32_t c) { uint32_t d; asm("fma.rn.relu.f16x2 %0, %1, %2, %3;" : "=r"(d) : "r"(a), "r"(b), "r"(c)); return d; }
__device__ __forceinline__ uint32_t hadd2(uint32_t a, uint32_t b) { uint32_t d; asm("add.rn.f16x2 %0, %1, %2;" : "=r"(d) : "r"(a), "r"(b)); return d; }
__device__ __forceinline__ uint32_t ex2_h2(uint32_t a) { uint32_t d; asm("ex2.approx.f16x2 %0, %1;" : "=r"(d) : "r"(a)); return d; }

__device__ __forceinline__ void mma_n96(float (&d)[48], uint64_t da, uint64_t db, int sd) {
  asm volatile("{\n.reg .pred p;\nsetp.ne.b32 p, %50, 0;\n"
   "wgmma.mma_async.sync.aligned.m64n96k16.f32.bf16.bf16 {%0,%1,%2,%3,%4,%5,%6,%7,%8,%9,%10,%11,%12,%13,%14,%15,%16,%17,%18,%19,%20,%21,%22,%23,%24,%25,%26,%27,%28,%29,%30,%31,%32,%33,%34,%35,%36,%37,%38,%39,%40,%41,%42,%43,%44,%45,%46,%47}, %48, %49, p, 1, 1, 0, 1;\n}\n"
   : "+f"(d[0]),"+f"(d[1]),"+f"(d[2]),"+f"(d[3]),"+f"(d[4]),"+f"(d[5]),"+f"(d[6]),"+f"(d[7]),"+f"(d[8]),"+f"(d[9]),"+f"(d[10]),"+f"(d[11]),"+f"(d[12]),"+f"(d[13]),"+f"(d[14]),"+f"(d[15]),"+f"(d[16]),"+f"(d[17]),"+f"(d[18]),"+f"(d[19]),"+f"(d[20]),"+f"(d[21]),"+f"(d[22]),"+f"(d[23]),"+f"(d[24]),"+f"(d[25]),"+f"(d[26]),"+f"(d[27]),"+f"(d[28]),"+f"(d[29]),"+f"(d[30]),"+f"(d[31]),"+f"(d[32]),"+f"(d[33]),"+f"(d[34]),"+f"(d[35]),"+f"(d[36]),"+f"(d[37]),"+f"(d[38]),"+f"(d[39]),"+f"(d[40]),"+f"(d[41]),"+f"(d[42]),"+f"(d[43]),"+f"(d[44]),"+f"(d[45]),"+f"(d[46]),"+f"(d[47])
   : "l"(da), "l"(db), "r"(sd));
}
__device__ __forceinline__ void mma_n88(float (&d)[44], uint64_t da, uint64_t db, int sd) {
  asm volatile("{\n.reg .pred p;\nsetp.ne.b32 p, %46, 0;\n"
   "wgmma.mma_async.sync.aligned.m64n88k16.f32.bf16.bf16 {%0,%1,%2,%3,%4,%5,%6,%7,%8,%9,%10,%11,%12,%13,%14,%15,%16,%17,%18,%19,%20,%21,%22,%23,%24,%25,%26,%27,%28,%29,%30,%31,%32,%33,%34,%35,%36,%37,%38,%39,%40,%41,%42,%43}, %44, %45, p, 1, 1, 0, 1;\n}\n"
   : "+f"(d[0]),"+f"(d[1]),"+f"(d[2]),"+f"(d[3]),"+f"(d[4]),"+f"(d[5]),"+f"(d[6]),"+f"(d[7]),"+f"(d[8]),"+f"(d[9]),"+f"(d[10]),"+f"(d[11]),"+f"(d[12]),"+f"(d[13]),"+f"(d[14]),"+f"(d[15]),"+f"(d[16]),"+f"(d[17]),"+f"(d[18]),"+f"(d[19]),"+f"(d[20]),"+f"(d[21]),"+f"(d[22]),"+f"(d[23]),"+f"(d[24]),"+f"(d[25]),"+f"(d[26]),"+f"(d[27]),"+f"(d[28]),"+f"(d[29]),"+f"(d[30]),"+f"(d[31]),"+f"(d[32]),"+f"(d[33]),"+f"(d[34]),"+f"(d[35]),"+f"(d[36]),"+f"(d[37]),"+f"(d[38]),"+f"(d[39]),"+f"(d[40]),"+f"(d[41]),"+f"(d[42]),"+f"(d[43])
   : "l"(da), "l"(db), "r"(sd));
}
__device__ __forceinline__ void mma_n128(float (&d)[64], uint64_t da, uint64_t db, int sd) {
  asm volatile("{\n.reg .pred p;\nsetp.ne.b32 p, %66, 0;\n"
   "wgmma.mma_async.sync.aligned.m64n128k16.f32.bf16.bf16 {%0,%1,%2,%3,%4,%5,%6,%7,%8,%9,%10,%11,%12,%13,%14,%15,%16,%17,%18,%19,%20,%21,%22,%23,%24,%25,%26,%27,%28,%29,%30,%31,%32,%33,%34,%35,%36,%37,%38,%39,%40,%41,%42,%43,%44,%45,%46,%47,%48,%49,%50,%51,%52,%53,%54,%55,%56,%57,%58,%59,%60,%61,%62,%63}, %64, %65, p, 1, 1, 0, 1;\n}\n"
   : "+f"(d[0]),"+f"(d[1]),"+f"(d[2]),"+f"(d[3]),"+f"(d[4]),"+f"(d[5]),"+f"(d[6]),"+f"(d[7]),"+f"(d[8]),"+f"(d[9]),"+f"(d[10]),"+f"(d[11]),"+f"(d[12]),"+f"(d[13]),"+f"(d[14]),"+f"(d[15]),"+f"(d[16]),"+f"(d[17]),"+f"(d[18]),"+f"(d[19]),"+f"(d[20]),"+f"(d[21]),"+f"(d[22]),"+f"(d[23]),"+f"(d[24]),"+f"(d[25]),"+f"(d[26]),"+f"(d[27]),"+f"(d[28]),"+f"(d[29]),"+f"(d[30]),"+f"(d[31]),"+f"(d[32]),"+f"(d[33]),"+f"(d[34]),"+f"(d[35]),"+f"(d[36]),"+f"(d[37]),"+f"(d[38]),"+f"(d[39]),"+f"(d[40]),"+f"(d[41]),"+f"(d[42]),"+f"(d[43]),"+f"(d[44]),"+f"(d[45]),"+f"(d[46]),"+f"(d[47]),"+f"(d[48]),"+f"(d[49]),"+f"(d[50]),"+f"(d[51]),"+f"(d[52]),"+f"(d[53]),"+f"(d[54]),"+f"(d[55]),"+f"(d[56]),"+f"(d[57]),"+f"(d[58]),"+f"(d[59]),"+f"(d[60]),"+f"(d[61]),"+f"(d[62]),"+f"(d[63])
   : "l"(da), "l"(db), "r"(sd));
}
__device__ __forceinline__ void mma_qk64(uint32_t (&d)[16], uint32_t a0, uint32_t a1, uint32_t a2, uint32_t a3, uint64_t dsc) {
  asm volatile("wgmma.mma_async.sync.aligned.m64n64k16.f16.f16.f16 {%0,%1,%2,%3,%4,%5,%6,%7,%8,%9,%10,%11,%12,%13,%14,%15}, {%16,%17,%18,%19}, %20, 0, 1, 1, 0;\n"
   : "=r"(d[0]),"=r"(d[1]),"=r"(d[2]),"=r"(d[3]),"=r"(d[4]),"=r"(d[5]),"=r"(d[6]),"=r"(d[7]),"=r"(d[8]),"=r"(d[9]),"=r"(d[10]),"=r"(d[11]),"=r"(d[12]),"=r"(d[13]),"=r"(d[14]),"=r"(d[15])
   : "r"(a0), "r"(a1), "r"(a2), "r"(a3), "l"(dsc));
}
__device__ __forceinline__ void mma_pv(uint32_t (&d)[6], uint32_t a0, uint32_t a1, uint32_t a2, uint32_t a3, uint64_t dsc) {
  asm volatile("wgmma.mma_async.sync.aligned.m64n24k16.f16.f16.f16 {%0,%1,%2,%3,%4,%5}, {%6,%7,%8,%9}, %10, 1, 1, 1, 1;\n"
   : "+r"(d[0]),"+r"(d[1]),"+r"(d[2]),"+r"(d[3]),"+r"(d[4]),"+r"(d[5])
   : "r"(a0), "r"(a1), "r"(a2), "r"(a3), "l"(dsc));
}
__device__ __forceinline__ void mma_pv_z(uint32_t (&d)[6], uint32_t a0, uint32_t a1, uint32_t a2, uint32_t a3, uint64_t dsc) {
  asm volatile("wgmma.mma_async.sync.aligned.m64n24k16.f16.f16.f16 {%0,%1,%2,%3,%4,%5}, {%6,%7,%8,%9}, %10, 0, 1, 1, 1;\n"
   : "=r"(d[0]),"=r"(d[1]),"=r"(d[2]),"=r"(d[3]),"=r"(d[4]),"=r"(d[5])
   : "r"(a0), "r"(a1), "r"(a2), "r"(a3), "l"(dsc));
}

__device__ __forceinline__ uint32_t exp2_fma(uint32_t y, uint32_t c1, uint32_t c2) {
    uint32_t r = hfma2_relu(y, 0x00800080u, c1);
    uint32_t g = hfma2(r, 0xF800F800u, c2);
    uint32_t w = hfma2_relu(g, 0x44004400u, y);
    uint32_t s = hfma2(w, w, 0x080B080Bu);
    return s + (r << 10);
}
__device__ __forceinline__ void exp_stage(const uint32_t (&s)[16], uint32_t (&p)[16], uint32_t c1, uint32_t c2) {
#pragma unroll
    for (int i = 0; i < 16; i++) p[i] = grp_is_mufu(i >> 1) ? ex2_h2(s[i]) : exp2_fma(s[i], c1, c2);
}
template <bool Z>
__device__ __forceinline__ void pv_stage(uint32_t (&oh)[6], const uint32_t (&p)[16], uint64_t dv) {
    if (Z) mma_pv_z(oh, p[0], p[1], p[2], p[3], dv); else mma_pv(oh, p[0], p[1], p[2], p[3], dv);
    mma_pv(oh, p[4], p[5], p[6], p[7], dv + 16);
    mma_pv(oh, p[8], p[9], p[10], p[11], dv + 32);
    mma_pv(oh, p[12], p[13], p[14], p[15], dv + 48);
}

__device__ __noinline__ void attention_exact(const __nv_bfloat16* __restrict__ x, const __nv_bfloat16* __restrict__ wqkv, int h, int row0,
                                             int tid, int barid, const float* gate_s) {
    __nv_bfloat16* kv = g_fb + (size_t)h * kS * 32;
    for (int key = tid; key < kS; key += 128) {
        float acc[32];
#pragma unroll
        for (int i = 0; i < 32; i++) acc[i] = 0.f;
        for (int d = 0; d < kD; d++) {
            float xv = __bfloat162float(x[(size_t)key * kD + d]);
            const uint4* wk = reinterpret_cast<const uint4*>(wqkv + (size_t)d * 1536 + 512 + h * 16);
            const uint4* wv = reinterpret_cast<const uint4*>(wqkv + (size_t)d * 1536 + 1024 + h * 16);
            uint4 w[4] = {wk[0], wk[1], wv[0], wv[1]};
#pragma unroll
            for (int i = 0; i < 4; i++) {
                acc[i * 8 + 0] += xv * bf_lo(w[i].x); acc[i * 8 + 1] += xv * bf_hi(w[i].x);
                acc[i * 8 + 2] += xv * bf_lo(w[i].y); acc[i * 8 + 3] += xv * bf_hi(w[i].y);
                acc[i * 8 + 4] += xv * bf_lo(w[i].z); acc[i * 8 + 5] += xv * bf_hi(w[i].z);
                acc[i * 8 + 6] += xv * bf_lo(w[i].w); acc[i * 8 + 7] += xv * bf_hi(w[i].w);
            }
        }
        uint4* dst = reinterpret_cast<uint4*>(kv + (size_t)key * 32);
#pragma unroll
        for (int i = 0; i < 4; i++)
            __stcg(dst + i, make_uint4(pack_bf2(acc[i * 8], acc[i * 8 + 1]), pack_bf2(acc[i * 8 + 2], acc[i * 8 + 3]),
                                       pack_bf2(acc[i * 8 + 4], acc[i * 8 + 5]), pack_bf2(acc[i * 8 + 6], acc[i * 8 + 7])));
    }
    __threadfence();
    bar_sync(barid, 128);
    const int rl = tid >> 1, par = tid & 1, row = row0 + rl;
    float q[16];
#pragma unroll
    for (int i = 0; i < 16; i++) q[i] = 0.f;
    for (int d = 0; d < kD; d++) {
        float xv = __bfloat162float(x[(size_t)row * kD + d]);
#pragma unroll
        for (int i = 0; i < 16; i++) q[i] += xv * __bfloat162float(wqkv[(size_t)d * 1536 + h * 16 + i]);
    }
#pragma unroll
    for (int i = 0; i < 16; i++) q[i] = bf_round(q[i]);
    auto score = [&](int key) {
        const uint4* kp = reinterpret_cast<const uint4*>(kv + (size_t)key * 32);
        uint4 a = __ldcg(kp), b = __ldcg(kp + 1);
        float s = q[0] * bf_lo(a.x) + q[1] * bf_hi(a.x) + q[2] * bf_lo(a.y) + q[3] * bf_hi(a.y) + q[4] * bf_lo(a.z) + q[5] * bf_hi(a.z) +
                  q[6] * bf_lo(a.w) + q[7] * bf_hi(a.w) + q[8] * bf_lo(b.x) + q[9] * bf_hi(b.x) + q[10] * bf_lo(b.y) + q[11] * bf_hi(b.y) +
                  q[12] * bf_lo(b.z) + q[13] * bf_hi(b.z) + q[14] * bf_lo(b.w) + q[15] * bf_hi(b.w);
        return bf_round(s) * 0.25f;
    };
    float m = -INFINITY;
    for (int key = par; key < kS; key += 2) m = fmaxf(m, score(key));
    m = fmaxf(m, __shfl_xor_sync(0xffffffffu, m, 1));
    float l = 0.f;
    for (int key = par; key < kS; key += 2) l += __expf(score(key) - m);
    l += __shfl_xor_sync(0xffffffffu, l, 1);
    const float il = 1.f / l;
    float o[16];
#pragma unroll
    for (int i = 0; i < 16; i++) o[i] = 0.f;
    for (int key = par; key < kS; key += 2) {
        float p = bf_round(__expf(score(key) - m) * il);
        const uint4* vp = reinterpret_cast<const uint4*>(kv + (size_t)key * 32 + 16);
        uint4 a = __ldcg(vp), b = __ldcg(vp + 1);
        o[0] += p * bf_lo(a.x); o[1] += p * bf_hi(a.x); o[2] += p * bf_lo(a.y); o[3] += p * bf_hi(a.y);
        o[4] += p * bf_lo(a.z); o[5] += p * bf_hi(a.z); o[6] += p * bf_lo(a.w); o[7] += p * bf_hi(a.w);
        o[8] += p * bf_lo(b.x); o[9] += p * bf_hi(b.x); o[10] += p * bf_lo(b.y); o[11] += p * bf_hi(b.y);
        o[12] += p * bf_lo(b.z); o[13] += p * bf_hi(b.z); o[14] += p * bf_lo(b.w); o[15] += p * bf_hi(b.w);
    }
    const float gt = gate_s[rl];
#pragma unroll
    for (int i = 0; i < 16; i++) o[i] = (o[i] + __shfl_xor_sync(0xffffffffu, o[i], 1)) * gt;
    uint4 v = par ? make_uint4(pack_bf2(o[8], o[9]), pack_bf2(o[10], o[11]), pack_bf2(o[12], o[13]), pack_bf2(o[14], o[15]))
                  : make_uint4(pack_bf2(o[0], o[1]), pack_bf2(o[2], o[3]), pack_bf2(o[4], o[5]), pack_bf2(o[6], o[7]));
    g_O[((row >> 6) * 64 + h * 2 + par) * 64 + rl] = v;
    bar_sync(barid, 128);
}

struct Params {
    const __nv_bfloat16 *x, *wqkv, *wo, *w1, *b1, *w2, *b2, *gw;
};

__device__ __forceinline__ void load_kv_chunk(uint32_t sb, int h, int c) {
    const uint4* src = g_KV + (h * 8 + c) * 1024;
    const uint32_t bar = sb + B_KVFULL + c * 8;
    mbar_expect(bar, 16384);
    bulk_g2s(sb + 57344 - c * 8192, src, 8192, bar);
    bulk_g2s(sb + 94208 - c * 4096, src + 512, 4096, bar);
    bulk_g2s(sb + 98304 + c * 4096, src + 768, 4096, bar);
}

__global__ void __cluster_dims__(2, 1, 1) __launch_bounds__(640, 1)
fused_kernel(const __grid_constant__ CUtensorMap tmX, const __grid_constant__ CUtensorMap tmWqkv, const __grid_constant__ CUtensorMap tmW1,
             const __grid_constant__ CUtensorMap tmW2, const __grid_constant__ CUtensorMap tmWo, const __grid_constant__ CUtensorMap tmOut,
             const Params P) {
    extern __shared__ __align__(1024) uint8_t smem[];
    const uint32_t sb = (uint32_t)__cvta_generic_to_shared(smem);
    const int wg = __shfl_sync(0xffffffffu, threadIdx.x >> 7, 0);
    const int warp = __shfl_sync(0xffffffffu, (threadIdx.x >> 5) & 3, 0);
    const int lane = threadIdx.x & 31, tid = threadIdx.x & 127, g = lane >> 2, t = lane & 3;
    const int cta = blockIdx.x, j = cta >> 4, mi = cta & 15, rank = cta & 1;
    const int hh = mi >> 3, qb = mi & 7;
    TLS(0);

    if (threadIdx.x == 512) {
        for (int i = 0; i < 8; i++) { mbar_init(sb + B_XFULL + i * 8, 1); mbar_init(sb + B_KVFULL + i * 8, 1); mbar_init(sb + B_KVEMPTY + i * 8, 4); }
        for (int i = 0; i < 4; i++) { mbar_init(sb + B_WFULL + i * 8, 1); mbar_init(sb + B_WEMPTY + i * 8, 8); mbar_init(sb + B_TAILA + i * 8, 1); }
        for (int i = 0; i < 3; i++) mbar_init(sb + B_FFULL + i * 8, 1);
        mbar_init(sb + B_AUX, 2); mbar_init(sb + B_GATE, 1); mbar_init(sb + B_TAILB, 1);
        asm volatile("fence.mbarrier_init.release.cluster;" ::: "memory");
        fence_async();
        for (int k = 0; k < 2; k++) {
            mbar_expect(sb + B_XFULL + k * 8, 16384);
            tma2d(sb + ((XREG >> (k * 4)) & 7) * 16384, &tmX, k * 64, mi * 128, sb + B_XFULL + k * 8);
        }
    }
    __syncwarp();
    asm volatile("barrier.cluster.arrive.relaxed.aligned;" ::: "memory");
    asm volatile("barrier.cluster.wait.aligned;" ::: "memory");

    if (wg < 4) {
        const int mh = wg & 1, nh = wg >> 1;
        {
            float acc[48];
#pragma unroll 1
            for (int s = 0; s < 8; s++) {
                const uint64_t da = mkdesc(sb + ((XREG >> (s * 4)) & 7) * 16384 + mh * 8192, 16, 1024, 1);
                const uint64_t db = mkdesc(sb + SM_RING + (s & 3) * SLOT + nh * 12288, 4096, 512, 2);
                mbar_wait(sb + B_XFULL + s * 8, 0);
                mbar_wait(sb + B_WFULL + (s & 3) * 8, (s >> 2) & 1);
                wg_fence();
                mma_n96(acc, da, db, s);
                mma_n96(acc, da + 2, db + 64, 1);
                mma_n96(acc, da + 4, db + 128, 1);
                mma_n96(acc, da + 6, db + 192, 1);
                wg_commit();
                wg_wait<1>();
                if (s > 0 && tid < 2) mbar_arrive_rank(sb + B_WEMPTY + ((s - 1) & 3) * 8, tid);
            }
            wg_wait<0>();
            if (tid < 2) mbar_arrive_rank(sb + B_WEMPTY + 3 * 8, tid);
            TLS(1);
            const int r16 = mi * 8 + mh * 4 + warp;
            const float ks0 = grp_is_mufu(warp * 2) ? 1.f : kLam, ks1 = grp_is_mufu(warp * 2 + 1) ? 1.f : kLam;
            const float vs0 = grp_is_mufu(warp * 2) ? 1.f : kPScale, vs1 = grp_is_mufu(warp * 2 + 1) ? 1.f : kPScale;
#pragma unroll
            for (int e = 0; e < 2; e++) {
                const int h = nh * 16 + j * 2 + e;
                const float* q = acc + e * 8; const float* k = acc + 16 + e * 8; const float* v = acc + 32 + e * 8;
                g_Q[(h * 128 + r16) * 32 + lane] = make_uint4(pack_h2(q[0] * kQScale, q[1] * kQScale), pack_h2(q[2] * kQScale, q[3] * kQScale),
                                                              pack_h2(q[4] * kQScale, q[5] * kQScale), pack_h2(q[6] * kQScale, q[7] * kQScale));
                uint32_t* base = reinterpret_cast<uint32_t*>(g_KV + (h * 8 + (r16 >> 4)) * 1024) + lane;
                uint32_t* kb = base + ((r16 & 8) ? 3072 : 1024) + (r16 & 7) * 128;
                kb[0] = pack_h2(k[0] * ks0, k[1] * ks0); kb[32] = pack_h2(k[4] * ks0, k[5] * ks0);
                kb[64] = pack_h2(k[2] * ks1, k[3] * ks1); kb[96] = pack_h2(k[6] * ks1, k[7] * ks1);
                uint32_t* vb = base + (r16 & 15) * 64;
                vb[0] = pack_h2(v[0] * vs0, v[1] * vs0); vb[32] = pack_h2(v[2] * vs1, v[3] * vs1);
                vb[2048] = pack_h2(v[4] * vs0, v[5] * vs0); vb[2080] = pack_h2(v[6] * vs1, v[7] * vs1);
                float n0 = k[0] * k[0] + k[1] * k[1] + k[4] * k[4] + k[5] * k[5], n1 = k[2] * k[2] + k[3] * k[3] + k[6] * k[6] + k[7] * k[7];
                n0 += __shfl_xor_sync(0xffffffffu, n0, 1); n1 += __shfl_xor_sync(0xffffffffu, n1, 1);
                n0 += __shfl_xor_sync(0xffffffffu, n0, 2); n1 += __shfl_xor_sync(0xffffffffu, n1, 2);
                float vm = fmaxf(fmaxf(fmaxf(fabsf(v[0]), fabsf(v[1])), fmaxf(fabsf(v[2]), fabsf(v[3]))), fmaxf(fmaxf(fabsf(v[4]), fabsf(v[5])), fmaxf(fabsf(v[6]), fabsf(v[7]))));
                const float km = warp_max_nonneg(__uint_as_float(max(__float_as_uint(n0), __float_as_uint(n1))));
                vm = warp_max_nonneg(vm);
                if (lane < 2) g_nrm[(h * 2 + lane) * 128 + r16] = lane ? vm : km;
            }
            bar_arrive(1, 544);
            TLS(2);
        }
        {
            const int f0 = (j * 2 + nh) * 88;
            uint32_t bias[11];
#pragma unroll
            for (int b = 0; b < 11; b++) bias[b] = (f0 + b * 8 < kF) ? *reinterpret_cast<const uint32_t*>(P.b1 + f0 + b * 8 + t * 2) : 0u;
            float acc[44];
#pragma unroll 1
            for (int s = 0; s < 8; s++) {
                const uint64_t da = mkdesc(sb + ((XREG >> (s * 4)) & 7) * 16384 + mh * 8192, 16, 1024, 1);
                const uint64_t db = mkdesc(sb + SM_RING + (s & 3) * SLOT + nh * 12288, 4096, 512, 2);
                mbar_wait(sb + B_WFULL + (s & 3) * 8, (s >> 2) & 1);
                wg_fence();
                mma_n88(acc, da, db, s);
                mma_n88(acc, da + 2, db + 64, 1);
                mma_n88(acc, da + 4, db + 128, 1);
                mma_n88(acc, da + 6, db + 192, 1);
                wg_commit();
                wg_wait<1>();
                if (s > 0 && tid < 2) mbar_arrive_rank(sb + B_WEMPTY + ((s - 1) & 3) * 8, tid);
            }
            wg_wait<0>();
            if (tid < 2) mbar_arrive_rank(sb + B_WEMPTY + 3 * 8, tid);
            TLS(3);
            uint32_t* hb = reinterpret_cast<uint32_t*>(g_H + ((mi * 2 + mh) * 172 + (j * 2 + nh) * 11) * 64) + warp * 64 + lane;
#pragma unroll
            for (int b = 0; b < 11; b++) {
                if (f0 + b * 8 < kF) {
                    const float b0 = bf_lo(bias[b]), b1 = bf_hi(bias[b]);
                    const float u0 = fmaxf(acc[b * 4] + b0, 0.f), u1 = fmaxf(acc[b * 4 + 1] + b1, 0.f);
                    const float u2 = fmaxf(acc[b * 4 + 2] + b0, 0.f), u3 = fmaxf(acc[b * 4 + 3] + b1, 0.f);
                    hb[b * 256] = pack_bf2(u0 * u0, u1 * u1);
                    hb[b * 256 + 32] = pack_bf2(u2 * u2, u3 * u3);
                }
            }
            bar_arrive(2, 544);
            TLS(4);
        }
        mbar_wait(sb + B_AUX, 0);
        uint32_t c1 = 0x00090009u, c2 = 0x253E253Eu;
        asm volatile("" : "+r"(c1), "+r"(c2));
#pragma unroll 1
        for (int r = 0; r < 2; r++) {
            const int h = r * 16 + j * 2 + hh;
            const uint4 qf = *reinterpret_cast<const uint4*>(smem + SM_Q + r * 8192 + (wg * 4 + warp) * 512 + lane * 16);
            uint32_t s[16], pa[16], pb[16], oh[6], o2[6];
            uint64_t dka = mkdesc(sb + 61440, 128, 256, 0), dkb = mkdesc(sb + 98304, 128, 256, 0), dv = mkdesc(sb + 57344, 128, 36864, 0);
            mbar_wait(sb + B_KVFULL, r);
            TLS(5 + r * 3);
            wg_fence();
            mma_qk64(s, qf.x, qf.y, qf.z, qf.w, dka);
            wg_commit();
            wg_wait<0>();
#pragma unroll
            for (int i = 0; i < 6; i++) { oh[i] = 0; o2[i] = 0; }
#pragma unroll 1
            for (int c = 0; c < 8; c++) {
                exp_stage(s, pa, c1, c2);
                wg_wait<0>();
#pragma unroll
                for (int i = 0; i < 6; i++) o2[i] = hadd2(o2[i], oh[i]);
                if (c > 0 && tid == 0) mbar_arrive(sb + B_KVEMPTY + (c - 1) * 8);
                wg_fence();
                mma_qk64(s, qf.x, qf.y, qf.z, qf.w, dka + 128); wg_commit();
                pv_stage<true>(oh, pa, dv); wg_commit();
                wg_wait<1>();

                exp_stage(s, pb, c1, c2);
                wg_fence();
                mma_qk64(s, qf.x, qf.y, qf.z, qf.w, dkb); wg_commit();
                pv_stage<false>(oh, pb, dv + 64); wg_commit();
                wg_wait<1>();

                exp_stage(s, pa, c1, c2);
                wg_fence();
                mma_qk64(s, qf.x, qf.y, qf.z, qf.w, dkb + 128); wg_commit();
                pv_stage<false>(oh, pa, dv + 128); wg_commit();
                wg_wait<1>();

                exp_stage(s, pb, c1, c2);
                if (c < 7) { mbar_wait(sb + B_KVFULL + (c + 1) * 8, r); dka -= 512; }
                wg_fence();
                mma_qk64(s, qf.x, qf.y, qf.z, qf.w, dka); wg_commit();
                pv_stage<false>(oh, pb, dv + 192); wg_commit();
                wg_wait<1>();
                dkb += 256;
                dv += (256ull << 32) - 512;
            }
            wg_wait<0>();
            if (tid == 0) mbar_arrive(sb + B_KVEMPTY + 7 * 8);
            TLS(6 + r * 3);
            float q0 = h_lo(qf.x) * h_lo(qf.x) + h_hi(qf.x) * h_hi(qf.x) + h_lo(qf.z) * h_lo(qf.z) + h_hi(qf.z) * h_hi(qf.z);
            float q1 = h_lo(qf.y) * h_lo(qf.y) + h_hi(qf.y) * h_hi(qf.y) + h_lo(qf.w) * h_lo(qf.w) + h_hi(qf.w) * h_hi(qf.w);
            q0 += __shfl_xor_sync(0xffffffffu, q0, 1); q1 += __shfl_xor_sync(0xffffffffu, q1, 1);
            q0 += __shfl_xor_sync(0xffffffffu, q0, 2); q1 += __shfl_xor_sync(0xffffffffu, q1, 2);
            const uint4 nk = *reinterpret_cast<const uint4*>(smem + SM_NRM + r * 1024 + lane * 16);
            const uint4 nv = *reinterpret_cast<const uint4*>(smem + SM_NRM + r * 1024 + 512 + lane * 16);
            const float km = __uint_as_float(__reduce_max_sync(0xffffffffu, max(max(nk.x, nk.y), max(nk.z, nk.w))));
            const float vm = __uint_as_float(__reduce_max_sync(0xffffffffu, max(max(nv.x, nv.y), max(nv.z, nv.w))));
            float o[8];
#pragma unroll
            for (int i = 0; i < 4; i++) { o[2 * i] = h_lo(o2[i]) + h_lo(oh[i]); o[2 * i + 1] = h_hi(o2[i]) + h_hi(oh[i]); }
            const float l0 = h_lo(o2[4]) + h_lo(oh[4]), l1 = h_lo(o2[5]) + h_lo(oh[5]);
            const float om = fmaxf(fmaxf(fmaxf(fabsf(o[0]), fabsf(o[1])), fmaxf(fabsf(o[2]), fabsf(o[3]))), fmaxf(fmaxf(fabsf(o[4]), fabsf(o[5])), fmaxf(fabsf(o[6]), fabsf(o[7]))));
            const float osum = o[0] + o[1] + o[2] + o[3] + o[4] + o[5] + o[6] + o[7];
            const bool ok = (q0 <= 4096.f) && (q1 <= 4096.f) && (km <= 16777216.f) && (vm >= 0.0009765625f) &&
                            (q0 * km <= 334.f) && (q1 * km <= 334.f) && (q0 * km <= 88.f || l0 >= 1024.f) && (q1 * km <= 88.f || l1 >= 1024.f) &&
                            (l0 <= 131000.f) && (l1 <= 131000.f) && (om <= 131000.f) && (osum == osum);
            if (r == 0) mbar_wait(sb + B_GATE, 0);
            const float* gs = reinterpret_cast<const float*>(smem + SM_GATE) + wg * 64;
            const float s0 = gs[warp * 16 + g] / l0, s1 = gs[warp * 16 + g + 8] / l1;
            uint32_t* ob = reinterpret_cast<uint32_t*>(g_O + ((qb * 4 + wg) * 64 + h * 2) * 64) + warp * 64 + lane;
            ob[0] = pack_bf2(o[0] * s0, o[1] * s0); ob[32] = pack_bf2(o[2] * s1, o[3] * s1);
            ob[256] = pack_bf2(o[4] * s0, o[5] * s0); ob[288] = pack_bf2(o[6] * s1, o[7] * s1);
            if (bar_or(4 + wg, 128, !ok)) attention_exact(P.x, P.wqkv, h, qb * 256 + wg * 64, tid, 8 + wg, gs);
            if (tid == 0) cnt_signal(CNT_O + r * 32 + qb * 4 + wg);
            TLS(7 + r * 3);
        }
    } else {
        const int u = j * 2 + hh, rb = qb * 4 + (u & 3), cb = u >> 2;
        unsigned epoch1 = 0;
        if (warp == 0) {
            if (lane == 0) {
                auto load_w = [&](int s) {
                    const uint32_t bar = sb + B_WFULL + (s & 3) * 8, dst = sb + SM_RING + (s & 3) * SLOT + rank * 12288;
                    mbar_expect(bar, SLOT);
                    if (s < 8) {
                        for (int p = 0; p < 3; p++) tma2d_mc(dst + p * 4096, &tmWqkv, p * 512 + rank * 256 + j * 32, s * 64, bar);
                    } else {
                        for (int p = 0; p < 3; p++) tma2d_mc(dst + p * 4096, &tmW1, (j * 2 + rank) * 88 + p * 32, (s - 8) * 64, bar);
                    }
                };
                auto load_x = [&](int k) {
                    mbar_expect(sb + B_XFULL + k * 8, 16384);
                    tma2d(sb + ((XREG >> (k * 4)) & 7) * 16384, &tmX, k * 64, mi * 128, sb + B_XFULL + k * 8);
                };
                load_w(0); load_w(1); load_x(2); load_w(2); load_x(3); load_w(3);
                for (int k = 4; k < 8; k++) load_x(k);
                epoch1 = (atomicAdd(g_cnt + CNT_TICKET * 32, 1u) >> 7) + 1;
                for (int s = 4; s < 16; s++) {
                    mbar_wait(sb + B_WEMPTY + (s & 3) * 8, ((s >> 2) - 1) & 1);
                    load_w(s);
                }
                cnt_wait(CNT_QKV + j, epoch1 * 16);
                fence_async();
                for (int c = 0; c < 4; c++) load_kv_chunk(sb, j * 2 + hh, c);
                mbar_wait(sb + B_WEMPTY + 0 * 8, 1);
                mbar_expect(sb + B_AUX, 2 * (8192 + 1024));
                for (int r = 0; r < 2; r++) {
                    const int h = r * 16 + j * 2 + hh;
                    bulk_g2s(sb + SM_Q + r * 8192, g_Q + (h * 128 + qb * 16) * 32, 8192, sb + B_AUX);
                    bulk_g2s(sb + SM_NRM + r * 1024, g_nrm + h * 256, 1024, sb + B_AUX);
                }
            }
            __syncwarp();
        } else if (warp == 1) {
            bar_sync(1, 544);
            if (lane == 0) cnt_signal(CNT_QKV + j);
        } else {
            const uint4 wa = *reinterpret_cast<const uint4*>(P.gw + lane * 8), wb = *reinterpret_cast<const uint4*>(P.gw + 256 + lane * 8);
            const int row0 = mi * 128 + j * 16 + (warp - 2) * 8;
            float mine = 0.f;
#pragma unroll
            for (int i = 0; i < 8; i++) {
                const uint4 xa = *reinterpret_cast<const uint4*>(P.x + (size_t)(row0 + i) * kD + lane * 8);
                const uint4 xb = *reinterpret_cast<const uint4*>(P.x + (size_t)(row0 + i) * kD + 256 + lane * 8);
                float a = bf_lo(xa.x) * bf_lo(wa.x) + bf_hi(xa.x) * bf_hi(wa.x) + bf_lo(xa.y) * bf_lo(wa.y) + bf_hi(xa.y) * bf_hi(wa.y) +
                          bf_lo(xa.z) * bf_lo(wa.z) + bf_hi(xa.z) * bf_hi(wa.z) + bf_lo(xa.w) * bf_lo(wa.w) + bf_hi(xa.w) * bf_hi(wa.w) +
                          bf_lo(xb.x) * bf_lo(wb.x) + bf_hi(xb.x) * bf_hi(wb.x) + bf_lo(xb.y) * bf_lo(wb.y) + bf_hi(xb.y) * bf_hi(wb.y) +
                          bf_lo(xb.z) * bf_lo(wb.z) + bf_hi(xb.z) * bf_hi(wb.z) + bf_lo(xb.w) * bf_lo(wb.w) + bf_hi(xb.w) * bf_hi(wb.w);
#pragma unroll
                for (int o = 16; o > 0; o >>= 1) a += __shfl_xor_sync(0xffffffffu, a, o);
                if (lane == i) mine = a;
            }
            if (lane < 8) g_gate[row0 + lane] = 1.f / (1.f + __expf(-mine));
            __syncwarp();
            if (lane == 0) cnt_signal(CNT_H + mi * 2 + (j >> 2));
            if (warp == 3 && lane == 0) {
                mbar_wait(sb + B_XFULL + 7 * 8, 0);
                l2_prefetch(reinterpret_cast<const uint8_t*>(P.w1) + cta * 11008, 11008);
                l2_prefetch(reinterpret_cast<const uint8_t*>(P.w2) + cta * 11008, 11008);
                l2_prefetch(reinterpret_cast<const uint8_t*>(P.wo) + cta * 4096, 4096);
            }
            __syncwarp();
        }
        bar_sync(3, 128);
        {
#pragma unroll
            for (int i = 0; i < 2; i++) {
                const int key = tid + i * 128;
                const uint32_t v = grp_is_mufu(key >> 3) ? 0x3C003C00u : kPScaleH2;
                *reinterpret_cast<uint4*>(smem + SM_ONES + key * 16) = make_uint4(v, v, v, v);
            }
            fence_async();
        }
        bar_sync(3, 128);
        auto load_b = [&](int st) {
            const uint32_t bar = sb + B_FFULL + (st % 3) * 8, dst = sb + SM_RING + (1 + st % 3) * SLOT + 8192;
            mbar_expect(bar, st == 21 ? SLOT - 4096 : SLOT);
            const CUtensorMap* tm = st < 22 ? &tmW2 : &tmWo;
            const int k0 = (st < 22 ? st : st - 22) * 64;
            tma2d(dst, tm, cb * 128, k0, bar);
            tma2d(dst + 8192, tm, cb * 128 + 64, k0, bar);
        };
        auto load_a = [&](int st) {
            const uint32_t bar = sb + B_FFULL + (st % 3) * 8, dst = sb + SM_RING + (1 + st % 3) * SLOT;
            if (st < 22) bulk_g2s(dst, g_H + (rb * 172 + st * 8) * 64, st == 21 ? 4096 : 8192, bar);
            else bulk_g2s(dst, g_O + (rb * 64 + (st - 22) * 8) * 64, 8192, bar);
        };
        int kvnext = 0;
        auto service_kv = [&]() {
            while (kvnext < 8 && mbar_test(sb + B_KVEMPTY + kvnext * 8, 0)) { load_kv_chunk(sb, 16 + j * 2 + hh, kvnext); kvnext++; }
        };
        if (warp == 0) {
            if (lane == 0) {
                mbar_arrive(sb + B_AUX);
                mbar_wait(sb + B_WEMPTY + 1 * 8, 1); load_b(0);
                mbar_wait(sb + B_WEMPTY + 2 * 8, 1); load_kv_chunk(sb, j * 2 + hh, 4); load_kv_chunk(sb, j * 2 + hh, 5); load_b(1);
                mbar_wait(sb + B_WEMPTY + 3 * 8, 1); load_kv_chunk(sb, j * 2 + hh, 6); load_kv_chunk(sb, j * 2 + hh, 7); load_b(2);
                for (int i = 0; i < 4; i++) cnt_wait(CNT_H + qb * 4 + i, epoch1 * 16);
                fence_async();
                mbar_expect(sb + B_GATE, 1024);
                bulk_g2s(sb + SM_GATE, g_gate + qb * 256, 1024, sb + B_GATE);
                load_a(0); load_a(1); load_a(2);
            }
            __syncwarp();
        } else if (warp == 1) {
            bar_sync(2, 544);
            if (lane < 2) cnt_signal(CNT_H + mi * 2 + lane);
            __syncwarp();
        }
        TLS(1);
        float acc[64];
#pragma unroll 1
        for (int st = 0; st < 26; st++) {
            const uint32_t slot = sb + SM_RING + (1 + st % 3) * SLOT;
            const uint64_t da = mkdesc(slot, 1024, 128, 0), db = mkdesc(slot + 8192, 8192, 1024, 1);
            mbar_wait(sb + B_FFULL + (st % 3) * 8, (st / 3) & 1);
            wg_fence(); mma_n128(acc, da, db, st); wg_commit(); wg_wait<0>();
            wg_fence(); mma_n128(acc, da + 128, db + 128, 1); wg_commit(); wg_wait<0>();
            if (st != 21) {
                wg_fence(); mma_n128(acc, da + 256, db + 256, 1); wg_commit(); wg_wait<0>();
                wg_fence(); mma_n128(acc, da + 384, db + 384, 1); wg_commit(); wg_wait<0>();
            }
            if (tid == 0) {
                service_kv();
                if (st + 3 < 26) {
                    load_b(st + 3);
                    if (st + 3 == 22) {
                        for (int n = 0; !cnt_test(CNT_O + rb, epoch1 * 16); n++) { service_kv(); if (n > (1 << 23)) __trap(); }
                        fence_async();
                    }
                    load_a(st + 3);
                }
            }
            __syncwarp();
            if (st == 21) {
                mbar_wait(sb + B_GATE, 0);
                const float* gs = reinterpret_cast<const float*>(smem + SM_GATE) + (u & 3) * 64 + warp * 16 + g;
                const float w0 = 1.f - gs[0], w1 = 1.f - gs[8];
#pragma unroll
                for (int b = 0; b < 16; b++) {
                    const uint32_t bb = *reinterpret_cast<const uint32_t*>(P.b2 + cb * 128 + b * 8 + t * 2);
                    acc[b * 4] = (acc[b * 4] + bf_lo(bb)) * w0; acc[b * 4 + 1] = (acc[b * 4 + 1] + bf_hi(bb)) * w0;
                    acc[b * 4 + 2] = (acc[b * 4 + 2] + bf_lo(bb)) * w1; acc[b * 4 + 3] = (acc[b * 4 + 3] + bf_hi(bb)) * w1;
                }
                TLS(2);
            }
        }
        TLS(3);
        if (tid == 0) {
            mbar_expect(sb + B_TAILB, 65536);
            for (int i = 0; i < 8; i++) tma2d(sb + SM_RING + SLOT + i * 8192, &tmWo, cb * 128 + (i & 1) * 64, 256 + (i >> 1) * 64, sb + B_TAILB);
            for (int n = 0; kvnext < 8; n++) { service_kv(); if (n > (1 << 26)) __trap(); }
            mbar_wait(sb + B_KVEMPTY + 3 * 8, 1);
            cnt_wait(CNT_O + 32 + rb, epoch1 * 16);
            fence_async();
            for (int i = 0; i < 4; i++) {
                mbar_expect(sb + B_TAILA + i * 8, 8192);
                bulk_g2s(sb + 32768 + i * 8192, g_O + (rb * 64 + 32 + i * 8) * 64, 8192, sb + B_TAILA + i * 8);
            }
        }
        __syncwarp();
        TLS(4);
        mbar_wait(sb + B_TAILB, 0);
#pragma unroll 1
        for (int i = 0; i < 4; i++) {
            const uint64_t da = mkdesc(sb + 32768 + i * 8192, 1024, 128, 0), db = mkdesc(sb + SM_RING + SLOT + i * 16384, 8192, 1024, 1);
            mbar_wait(sb + B_TAILA + i * 8, 0);
            wg_fence();
            mma_n128(acc, da, db, 1);
            mma_n128(acc, da + 128, db + 128, 1);
            mma_n128(acc, da + 256, db + 256, 1);
            mma_n128(acc, da + 384, db + 384, 1);
            wg_commit();
        }
        wg_wait<0>();
        bar_sync(3, 128);
        TLS(5);
        {
            const int row = warp * 16 + ((lane >> 3) & 1) * 8 + (lane & 7);
#pragma unroll
            for (int b = 0; b < 16; b += 2) {
                const int cbk = b + (lane >> 4);
                const uint32_t addr = sb + 32768 + (cbk >> 3) * 8192 + row * 128 + (((cbk & 7) ^ (row & 7)) << 4);
                asm volatile("stmatrix.sync.aligned.m8n8.x4.shared.b16 [%0], {%1, %2, %3, %4};" ::"r"(addr),
                             "r"(pack_bf2(acc[b * 4], acc[b * 4 + 1])), "r"(pack_bf2(acc[b * 4 + 2], acc[b * 4 + 3])),
                             "r"(pack_bf2(acc[b * 4 + 4], acc[b * 4 + 5])), "r"(pack_bf2(acc[b * 4 + 6], acc[b * 4 + 7])) : "memory");
            }
            fence_async();
            bar_sync(3, 128);
            if (tid == 0) {
                tma2d_store(&tmOut, sb + 32768, cb * 128, rb * 64);
                tma2d_store(&tmOut, sb + 32768 + 8192, cb * 128 + 64, rb * 64);
                asm volatile("cp.async.bulk.commit_group;" ::: "memory");
                asm volatile("cp.async.bulk.wait_group 0;" ::: "memory");
            }
        }
        TLS(6);
    }
}

typedef CUresult (*EncodeFn)(CUtensorMap*, CUtensorMapDataType, cuuint32_t, void*, const cuuint64_t*, const cuuint64_t*, const cuuint32_t*,
                             const cuuint32_t*, CUtensorMapInterleave, CUtensorMapSwizzle, CUtensorMapL2promotion, CUtensorMapFloatOOBfill);

void make_map(EncodeFn fn, CUtensorMap* tm, const void* ptr, uint64_t cols, uint64_t rows, uint32_t bc, uint32_t br, CUtensorMapSwizzle sw) {
    cuuint64_t dims[2] = {cols, rows}, strides[1] = {cols * 2};
    cuuint32_t box[2] = {bc, br}, es[2] = {1, 1};
    fn(tm, CU_TENSOR_MAP_DATA_TYPE_BFLOAT16, 2, const_cast<void*>(ptr), dims, strides, box, es, CU_TENSOR_MAP_INTERLEAVE_NONE, sw,
       CU_TENSOR_MAP_L2_PROMOTION_L2_128B, CU_TENSOR_MAP_FLOAT_OOB_FILL_NONE);
}

}

extern "C" void kernel_launch(void* const* d_in, const int* in_sizes, int n_in, void* d_out, int out_size) {
    (void)in_sizes; (void)n_in; (void)out_size;
    Params P;
    P.x = (const __nv_bfloat16*)d_in[0]; P.wqkv = (const __nv_bfloat16*)d_in[1]; P.wo = (const __nv_bfloat16*)d_in[2];
    P.w1 = (const __nv_bfloat16*)d_in[4]; P.b1 = (const __nv_bfloat16*)d_in[5]; P.w2 = (const __nv_bfloat16*)d_in[6];
    P.b2 = (const __nv_bfloat16*)d_in[7]; P.gw = (const __nv_bfloat16*)d_in[8];
    void* fp = nullptr;
    cudaDriverEntryPointQueryResult qr;
    cudaGetDriverEntryPoint("cuTensorMapEncodeTiled", &fp, cudaEnableDefault, &qr);
    EncodeFn fn = (EncodeFn)fp;
    CUtensorMap tmX, tmWqkv, tmW1, tmW2, tmWo, tmOut;
    make_map(fn, &tmX, P.x, kD, kS, 64, 128, CU_TENSOR_MAP_SWIZZLE_128B);
    make_map(fn, &tmWqkv, P.wqkv, 1536, kD, 32, 64, CU_TENSOR_MAP_SWIZZLE_64B);
    make_map(fn, &tmW1, P.w1, kF, kD, 32, 64, CU_TENSOR_MAP_SWIZZLE_64B);
    make_map(fn, &tmW2, P.w2, kD, kF, 64, 64, CU_TENSOR_MAP_SWIZZLE_128B);
    make_map(fn, &tmWo, P.wo, kD, kD, 64, 64, CU_TENSOR_MAP_SWIZZLE_128B);
    make_map(fn, &tmOut, d_out, kD, kS, 64, 64, CU_TENSOR_MAP_SWIZZLE_128B);
    cudaFuncSetAttribute(fused_kernel, cudaFuncAttributeMaxDynamicSharedMemorySize, SMEM_BYTES);
    fused_kernel<<<128, 640, SMEM_BYTES>>>(tmX, tmWqkv, tmW1, tmW2, tmWo, tmOut, P);
}
```

```cpp
#include <cuda_runtime.h>
#include <cuda_bf16.h>
#include <cuda_fp16.h>
#include <cuda.h>
#include <stdint.h>

#define HT 7
namespace {

constexpr int kS = 2048, kD = 512, kF = 1376;

__device__ __align__(128) uint4 g_Q[32 * 128 * 32];
__device__ __align__(128) uint4 g_KV[32 * 8 * 1024];
__device__ __align__(128) float g_nrm[32 * 3 * 128];
__device__ __align__(128) uint4 g_H[32 * 176 * 64];
__device__ __align__(128) uint4 g_O[32 * 32 * 64];
__device__ __align__(128) uint4 g_O1[32 * 16 * 128];
__device__ __align__(128) float g_gate[kS];
__device__ __align__(128) __nv_bfloat16 g_fb[32 * kS * 32];
__device__ __align__(128) unsigned g_cnt[(1 + 16 + 32 + 32) * 32];
constexpr int CNT_TICKET = 0, CNT_QKV = 1, CNT_H = 17, CNT_O = 49;
#define TLS(i)
#define TLW(i)
#define TLDUMP()
#define TLC(i)
#define TLEXTRA 0

constexpr uint32_t SM_RING = 131072;
constexpr uint32_t SLOT = 24576;
constexpr uint32_t SM_ONES = SM_RING;
constexpr uint32_t SM_Q = SM_RING + 4096;
constexpr uint32_t SM_NRM = SM_RING + 20480;
constexpr uint32_t SM_GATE = SM_RING + 23552;
constexpr uint32_t SM_BAR = SM_RING + 4 * SLOT;
constexpr uint32_t B_XFULL = SM_BAR, B_WFULL = B_XFULL + 64, B_WEMPTY = B_WFULL + 32, B_KVFULL = B_WEMPTY + 32,
                   B_KVEMPTY = B_KVFULL + 80, B_AUX = B_KVEMPTY + 64, B_GATE = B_AUX + 8, B_FFULL = B_GATE + 8,
                   B_TAILB = B_FFULL + 24, B_TAILA = B_TAILB + 8, B_FLAG = B_TAILA + 32, B_ODONE = B_FLAG + 8, B_AUX1 = B_ODONE + 8, B_XDEAD = B_AUX1 + 8, B_END = B_XDEAD + 8, B_TAILGO = B_TAILB;
constexpr uint32_t SM_LMIN = B_END;
constexpr uint32_t SM_B1 = SM_BAR + 512;
constexpr uint32_t SM_EPOCH = SM_BAR + 872, SM_TICK = SM_BAR + 876, SM_ORDER = SM_BAR + 880;
constexpr uint32_t SM_NST = SM_BAR + 896;
constexpr uint32_t SMEM_BYTES = SM_BAR + 1280 + TLEXTRA;
static_assert(B_END - SM_BAR <= 48 * 8 && SM_LMIN + 128 <= SM_B1, "barrier area");
__host__ __device__ constexpr uint64_t bar_counts(int n) {
    uint64_t r = 0;
    for (int i = 0; i < 16; i++) {
        const uint32_t a = SM_BAR + (n * 16 + i) * 8;
        r |= (uint64_t)(((a >= B_WEMPTY && a < B_KVFULL) || (a >= B_KVEMPTY - 8 && a < B_AUX)) ? 8 : a == B_ODONE ? 4 : a == B_AUX ? 3 : a == B_GATE ? 2 : 1) << (i * 4);
    }
    return r;
}
__host__ __device__ constexpr uint32_t tailb_off(int i) { return i < 3 ? 32768u * (i + 1) : SM_Q; }
constexpr uint32_t SB0 = 1024;
constexpr uint32_t XREG = 0x37521640u;

constexpr float kQScale = 0.25f * 1.4426950408889634f;
constexpr float kLam = 1.0f / 128.0f;
constexpr float kPScale = 7.578125f;
constexpr uint32_t kPScaleH2 = 0x47944794u;
#define PAT 0xA4A4A4A4u
__host__ __device__ constexpr bool grp_is_mufu(int grp) { return ((PAT >> (grp & 31)) & 1) != 0; }

__device__ __forceinline__ void wg_fence() { asm volatile("wgmma.fence.sync.aligned;" ::: "memory"); }
__device__ __forceinline__ void wg_commit() { asm volatile("wgmma.commit_group.sync.aligned;" ::: "memory"); }
template <int N> __device__ __forceinline__ void wg_wait() { asm volatile("wgmma.wait_group.sync.aligned %0;" ::"n"(N) : "memory"); }
__host__ __device__ constexpr uint64_t mkdesc(uint32_t addr, uint32_t lbo, uint32_t sbo, uint32_t swz) {
    return (uint64_t)((addr & 0x3FFFF) >> 4) | ((uint64_t)(lbo >> 4) << 16) | ((uint64_t)(sbo >> 4) << 32) | ((uint64_t)swz << 62);
}
__device__ __forceinline__ uint64_t join64(uint32_t lo, uint32_t hi) { uint64_t r; asm("mov.b64 %0, {%1, %2};" : "=l"(r) : "r"(lo), "r"(hi)); return r; }
__device__ __forceinline__ void mbar_arrive_rank(uint32_t a, uint32_t rank) {
    asm volatile("{\n.reg .b32 r;\nmapa.shared::cluster.u32 r, %0, %1;\nmbarrier.arrive.shared::cluster.b64 _, [r];\n}" ::"r"(a), "r"(rank) : "memory");
}
__device__ __forceinline__ bool mbar_test(uint32_t a, uint32_t par) {
    uint32_t ok;
    asm volatile("{\n.reg .pred p;\nmbarrier.test_wait.parity.shared::cta.b64 p, [%1], %2;\nselp.u32 %0, 1, 0, p;\n}" : "=r"(ok) : "r"(a), "r"(par) : "memory");
    return __all_sync(0xffffffffu, ok != 0);
}
__device__ __forceinline__ void mbar_wait(uint32_t a, uint32_t par) {
    asm volatile(
        "{\n.reg .pred p;\n.reg .u32 n;\n"
        "mbarrier.try_wait.parity.shared::cta.b64 p, [%0], %1;\n"
        "@p bra.uni D_%=;\n"
        "mov.u32 n, 0;\n"
        "L_%=:\n"
        "mbarrier.try_wait.parity.shared::cta.b64 p, [%0], %1;\n"
        "@p bra.uni D_%=;\n"
        "add.u32 n, n, 1;\n"
        "setp.lt.u32 p, n, 0x4000000;\n"
        "@p bra.uni L_%=;\n"
        "D_%=:\n}" ::"r"(a), "r"(par) : "memory");
}
#define ELECT "{\n.reg .pred e;\nelect.sync _|e, 0xffffffff;\n@e "
__device__ __forceinline__ void e_init(uint32_t a, uint32_t c) { asm volatile(ELECT "mbarrier.init.shared::cta.b64 [%0], %1;\n}" ::"r"(a), "r"(c) : "memory"); }
__device__ __forceinline__ void e_expect(uint32_t a, uint32_t b) { asm volatile(ELECT "mbarrier.arrive.expect_tx.shared::cta.b64 _, [%0], %1;\n}" ::"r"(a), "r"(b) : "memory"); }
__device__ __forceinline__ void e_arrive(uint32_t a) { asm volatile(ELECT "mbarrier.arrive.shared::cta.b64 _, [%0];\n}" ::"r"(a) : "memory"); }
__device__ __forceinline__ void e_bulk(uint32_t dst, const void* src, uint32_t bytes, uint32_t bar) {
    asm volatile(ELECT "cp.async.bulk.shared::cluster.global.mbarrier::complete_tx::bytes [%0], [%1], %2, [%3];\n}" ::"r"(dst), "l"(src), "r"(bytes), "r"(bar) : "memory");
}
__device__ __forceinline__ void e_bulk_mc(uint32_t dst, const void* src, uint32_t bytes, uint32_t bar) {
    asm volatile(ELECT "cp.async.bulk.shared::cluster.global.mbarrier::complete_tx::bytes.multicast::cluster [%0], [%1], %2, [%3], %4;\n}" ::"r"(dst), "l"(src), "r"(bytes), "r"(bar), "h"((uint16_t)3) : "memory");
}
__device__ __forceinline__ void e_bulk_store(void* dst, uint32_t src, uint32_t bytes) {
    asm volatile(ELECT "cp.async.bulk.global.shared::cta.bulk_group [%0], [%1], %2;\n}" ::"l"(dst), "r"(src), "r"(bytes) : "memory");
}
__device__ __forceinline__ void e_tma2d(uint32_t dst, const CUtensorMap* tm, int c0, int c1, uint32_t bar) {
    asm volatile(ELECT "cp.async.bulk.tensor.2d.shared::cluster.global.mbarrier::complete_tx::bytes [%0], [%1, {%3, %4}], [%2];\n}" ::"r"(dst), "l"(tm), "r"(bar), "r"(c0), "r"(c1) : "memory");
}
__device__ __forceinline__ void e_tma3d(uint32_t dst, const CUtensorMap* tm, int c0, int c1, int c2, uint32_t bar) {
    asm volatile(ELECT "cp.async.bulk.tensor.3d.shared::cluster.global.mbarrier::complete_tx::bytes [%0], [%1, {%3, %4, %5}], [%2];\n}" ::"r"(dst), "l"(tm), "r"(bar), "r"(c0), "r"(c1), "r"(c2) : "memory");
}
__device__ __forceinline__ void e_tma2d_mc(uint32_t dst, const CUtensorMap* tm, int c0, int c1, uint32_t bar) {
    asm volatile(ELECT "cp.async.bulk.tensor.2d.shared::cluster.global.mbarrier::complete_tx::bytes.multicast::cluster [%0], [%1, {%3, %4}], [%2], %5;\n}" ::"r"(dst), "l"(tm), "r"(bar), "r"(c0), "r"(c1), "h"((uint16_t)3) : "memory");
}
__device__ __forceinline__ void e_prefetch(const void* p, uint32_t bytes) { asm volatile(ELECT "cp.async.bulk.prefetch.L2.global [%0], %1;\n}" ::"l"(p), "r"(bytes) : "memory"); }
__device__ __forceinline__ void e_signal(int idx) { asm volatile(ELECT "red.release.gpu.global.add.u32 [%0], 1;\n}" ::"l"(g_cnt + idx * 32) : "memory"); }
__device__ __forceinline__ void fence_async_smem() { asm volatile("fence.proxy.async.shared::cta;" ::: "memory"); }
__device__ __forceinline__ void fence_async_gmem() { asm volatile("fence.proxy.async.global;" ::: "memory"); }
__device__ __forceinline__ void signal_n(int idx, int n, int lane) {
    if (lane < n) asm volatile("fence.acq_rel.gpu;\nred.relaxed.gpu.global.add.u32 [%0], 1;" ::"l"(g_cnt + (idx + lane) * 32) : "memory");
    __syncwarp();
}
__device__ __forceinline__ void stsm4(uint32_t a, uint32_t r0, uint32_t r1, uint32_t r2, uint32_t r3) {
    asm volatile("stmatrix.sync.aligned.m8n8.x4.shared.b16 [%0], {%1, %2, %3, %4};" ::"r"(a), "r"(r0), "r"(r1), "r"(r2), "r"(r3) : "memory");
}
__device__ __forceinline__ void bar_sync(int id, int n) { asm volatile("bar.sync %0, %1;" ::"r"(id), "r"(n) : "memory"); }
__device__ __forceinline__ void bar_arrive(int id, int n) { asm volatile("bar.arrive %0, %1;" ::"r"(id), "r"(n) : "memory"); }
__device__ __forceinline__ bool bar_or(int id, int n, bool v) {
    uint32_t r;
    asm volatile("{\n.reg .pred p, q;\nsetp.ne.u32 p, %3, 0;\nbar.red.or.pred q, %1, %2, p;\nselp.u32 %0, 1, 0, q;\n}" : "=r"(r) : "r"(id), "r"(n), "r"((uint32_t)v) : "memory");
    return r != 0;
}
__device__ __forceinline__ bool cnt_test(int idx, unsigned target) {
    unsigned v;
    asm volatile("ld.acquire.gpu.global.u32 %0, [%1];" : "=r"(v) : "l"(g_cnt + idx * 32) : "memory");
    return __all_sync(0xffffffffu, (int)(v - target) >= 0);
}
__device__ __forceinline__ void cnt_wait(int idx, unsigned target) {
    for (int n = 0; n < (1 << 22) && !cnt_test(idx, target); n++) {}
}
__device__ __forceinline__ void st_relaxed(uint32_t* p, uint32_t v) { asm volatile("st.relaxed.gpu.global.u32 [%0], %1;" ::"l"(p), "r"(v) : "memory"); }
__device__ __forceinline__ void st_relaxed4(uint4* p, uint32_t a, uint32_t b, uint32_t c, uint32_t d) {
    asm volatile("st.relaxed.gpu.global.v4.u32 [%0], {%1, %2, %3, %4};" ::"l"(p), "r"(a), "r"(b), "r"(c), "r"(d) : "memory");
}
__device__ __forceinline__ uint4 ld_relaxed4(const uint4* p) {
    uint4 v;
    asm volatile("ld.relaxed.gpu.global.v4.u32 {%0, %1, %2, %3}, [%4];" : "=r"(v.x), "=r"(v.y), "=r"(v.z), "=r"(v.w) : "l"(p) : "memory");
    return v;
}
__device__ __forceinline__ uint32_t pack_h2(float lo, float hi) { uint32_t r; asm("cvt.rn.f16x2.f32 %0, %1, %2;" : "=r"(r) : "f"(hi), "f"(lo)); return r; }
__device__ __forceinline__ uint32_t pack_bf2(float lo, float hi) { uint32_t r; asm("cvt.rn.bf16x2.f32 %0, %1, %2;" : "=r"(r) : "f"(hi), "f"(lo)); return r; }
__device__ __forceinline__ float h_lo(uint32_t v) { return __low2float(*reinterpret_cast<__half2*>(&v)); }
__device__ __forceinline__ float h_hi(uint32_t v) { return __high2float(*reinterpret_cast<__half2*>(&v)); }
__device__ __forceinline__ float bf_lo(uint32_t v) { return __uint_as_float(v << 16); }
__device__ __forceinline__ float bf_hi(uint32_t v) { return __uint_as_float(v & 0xffff0000u); }
__device__ __forceinline__ float rcp(float v) { float r; asm("rcp.approx.ftz.f32 %0, %1;" : "=f"(r) : "f"(v)); return r; }
__device__ __forceinline__ float bf_round(float v) { return __bfloat162float(__float2bfloat16_rn(v)); }
__device__ __forceinline__ uint32_t relu_sq(uint32_t h, uint32_t b) {
    uint32_t d;
    asm("{\n.reg .b32 r;\nfma.rn.relu.bf16x2 r, %1, %2, %3;\nmul.rn.bf16x2 %0, r, r;\n}" : "=r"(d) : "r"(h), "r"(0x3F803F80u), "r"(b));
    return d;
}
__device__ __forceinline__ float ssq(uint32_t v) { return h_lo(v) * h_lo(v) + h_hi(v) * h_hi(v); }
__device__ __forceinline__ uint32_t max_row_norm2(const uint32_t* a, float s0, float s1) {
    float n0 = (ssq(a[0]) + ssq(a[2])) * s0, n1 = (ssq(a[1]) + ssq(a[3])) * s1;
    n0 += __shfl_xor_sync(0xffffffffu, n0, 1); n1 += __shfl_xor_sync(0xffffffffu, n1, 1);
    n0 += __shfl_xor_sync(0xffffffffu, n0, 2); n1 += __shfl_xor_sync(0xffffffffu, n1, 2);
    return __reduce_max_sync(0xffffffffu, max(__float_as_uint(n0), __float_as_uint(n1)));
}
__device__ __forceinline__ uint32_t hfma2(uint32_t a, uint32_t b, uint32_t c) { uint32_t d; asm("fma.rn.f16x2 %0, %1, %2, %3;" : "=r"(d) : "r"(a), "r"(b), "r"(c)); return d; }
__device__ __forceinline__ uint32_t hfma2_relu(uint32_t a, uint32_t b, uint32_t c) { uint32_t d; asm("fma.rn.relu.f16x2 %0, %1, %2, %3;" : "=r"(d) : "r"(a), "r"(b), "r"(c)); return d; }
__device__ __forceinline__ uint32_t hadd2(uint32_t a, uint32_t b) { uint32_t d; asm("add.rn.f16x2 %0, %1, %2;" : "=r"(d) : "r"(a), "r"(b)); return d; }
__device__ __forceinline__ uint32_t ex2_h2(uint32_t a) { uint32_t d; asm("ex2.approx.f16x2 %0, %1;" : "=r"(d) : "r"(a)); return d; }

__device__ __forceinline__ void mma_n96(float (&d)[48], uint64_t da, uint64_t db, int sd) {
  asm volatile("{\n.reg .pred p;\nsetp.ne.b32 p, %50, 0;\n"
   "wgmma.mma_async.sync.aligned.m64n96k16.f32.bf16.bf16 {%0,%1,%2,%3,%4,%5,%6,%7,%8,%9,%10,%11,%12,%13,%14,%15,%16,%17,%18,%19,%20,%21,%22,%23,%24,%25,%26,%27,%28,%29,%30,%31,%32,%33,%34,%35,%36,%37,%38,%39,%40,%41,%42,%43,%44,%45,%46,%47}, %48, %49, p, 1, 1, 0, 1;\n}\n"
   : "+f"(d[0]),"+f"(d[1]),"+f"(d[2]),"+f"(d[3]),"+f"(d[4]),"+f"(d[5]),"+f"(d[6]),"+f"(d[7]),"+f"(d[8]),"+f"(d[9]),"+f"(d[10]),"+f"(d[11]),"+f"(d[12]),"+f"(d[13]),"+f"(d[14]),"+f"(d[15]),"+f"(d[16]),"+f"(d[17]),"+f"(d[18]),"+f"(d[19]),"+f"(d[20]),"+f"(d[21]),"+f"(d[22]),"+f"(d[23]),"+f"(d[24]),"+f"(d[25]),"+f"(d[26]),"+f"(d[27]),"+f"(d[28]),"+f"(d[29]),"+f"(d[30]),"+f"(d[31]),"+f"(d[32]),"+f"(d[33]),"+f"(d[34]),"+f"(d[35]),"+f"(d[36]),"+f"(d[37]),"+f"(d[38]),"+f"(d[39]),"+f"(d[40]),"+f"(d[41]),"+f"(d[42]),"+f"(d[43]),"+f"(d[44]),"+f"(d[45]),"+f"(d[46]),"+f"(d[47])
   : "l"(da), "l"(db), "r"(sd));
}
__device__ __forceinline__ void mma_n88(float (&d)[44], uint64_t da, uint64_t db, int sd) {
  asm volatile("{\n.reg .pred p;\nsetp.ne.b32 p, %46, 0;\n"
   "wgmma.mma_async.sync.aligned.m64n88k16.f32.bf16.bf16 {%0,%1,%2,%3,%4,%5,%6,%7,%8,%9,%10,%11,%12,%13,%14,%15,%16,%17,%18,%19,%20,%21,%22,%23,%24,%25,%26,%27,%28,%29,%30,%31,%32,%33,%34,%35,%36,%37,%38,%39,%40,%41,%42,%43}, %44, %45, p, 1, 1, 0, 1;\n}\n"
   : "+f"(d[0]),"+f"(d[1]),"+f"(d[2]),"+f"(d[3]),"+f"(d[4]),"+f"(d[5]),"+f"(d[6]),"+f"(d[7]),"+f"(d[8]),"+f"(d[9]),"+f"(d[10]),"+f"(d[11]),"+f"(d[12]),"+f"(d[13]),"+f"(d[14]),"+f"(d[15]),"+f"(d[16]),"+f"(d[17]),"+f"(d[18]),"+f"(d[19]),"+f"(d[20]),"+f"(d[21]),"+f"(d[22]),"+f"(d[23]),"+f"(d[24]),"+f"(d[25]),"+f"(d[26]),"+f"(d[27]),"+f"(d[28]),"+f"(d[29]),"+f"(d[30]),"+f"(d[31]),"+f"(d[32]),"+f"(d[33]),"+f"(d[34]),"+f"(d[35]),"+f"(d[36]),"+f"(d[37]),"+f"(d[38]),"+f"(d[39]),"+f"(d[40]),"+f"(d[41]),"+f"(d[42]),"+f"(d[43])
   : "l"(da), "l"(db), "r"(sd));
}
__device__ __forceinline__ void mma_n128(float (&d)[64], uint64_t da, uint64_t db, int sd) {
  asm volatile("{\n.reg .pred p;\nsetp.ne.b32 p, %66, 0;\n"
   "wgmma.mma_async.sync.aligned.m64n128k16.f32.bf16.bf16 {%0,%1,%2,%3,%4,%5,%6,%7,%8,%9,%10,%11,%12,%13,%14,%15,%16,%17,%18,%19,%20,%21,%22,%23,%24,%25,%26,%27,%28,%29,%30,%31,%32,%33,%34,%35,%36,%37,%38,%39,%40,%41,%42,%43,%44,%45,%46,%47,%48,%49,%50,%51,%52,%53,%54,%55,%56,%57,%58,%59,%60,%61,%62,%63}, %64, %65, p, 1, 1, 0, 1;\n}\n"
   : "+f"(d[0]),"+f"(d[1]),"+f"(d[2]),"+f"(d[3]),"+f"(d[4]),"+f"(d[5]),"+f"(d[6]),"+f"(d[7]),"+f"(d[8]),"+f"(d[9]),"+f"(d[10]),"+f"(d[11]),"+f"(d[12]),"+f"(d[13]),"+f"(d[14]),"+f"(d[15]),"+f"(d[16]),"+f"(d[17]),"+f"(d[18]),"+f"(d[19]),"+f"(d[20]),"+f"(d[21]),"+f"(d[22]),"+f"(d[23]),"+f"(d[24]),"+f"(d[25]),"+f"(d[26]),"+f"(d[27]),"+f"(d[28]),"+f"(d[29]),"+f"(d[30]),"+f"(d[31]),"+f"(d[32]),"+f"(d[33]),"+f"(d[34]),"+f"(d[35]),"+f"(d[36]),"+f"(d[37]),"+f"(d[38]),"+f"(d[39]),"+f"(d[40]),"+f"(d[41]),"+f"(d[42]),"+f"(d[43]),"+f"(d[44]),"+f"(d[45]),"+f"(d[46]),"+f"(d[47]),"+f"(d[48]),"+f"(d[49]),"+f"(d[50]),"+f"(d[51]),"+f"(d[52]),"+f"(d[53]),"+f"(d[54]),"+f"(d[55]),"+f"(d[56]),"+f"(d[57]),"+f"(d[58]),"+f"(d[59]),"+f"(d[60]),"+f"(d[61]),"+f"(d[62]),"+f"(d[63])
   : "l"(da), "l"(db), "r"(sd));
}
__device__ __forceinline__ void mma_qk64(uint32_t (&d)[16], uint32_t a0, uint32_t a1, uint32_t a2, uint32_t a3, uint64_t dsc) {
  asm volatile("wgmma.mma_async.sync.aligned.m64n64k16.f16.f16.f16 {%0,%1,%2,%3,%4,%5,%6,%7,%8,%9,%10,%11,%12,%13,%14,%15}, {%16,%17,%18,%19}, %20, 0, 1, 1, 0;\n"
   : "=r"(d[0]),"=r"(d[1]),"=r"(d[2]),"=r"(d[3]),"=r"(d[4]),"=r"(d[5]),"=r"(d[6]),"=r"(d[7]),"=r"(d[8]),"=r"(d[9]),"=r"(d[10]),"=r"(d[11]),"=r"(d[12]),"=r"(d[13]),"=r"(d[14]),"=r"(d[15])
   : "r"(a0), "r"(a1), "r"(a2), "r"(a3), "l"(dsc));
}
__device__ __forceinline__ void mma_pv(uint32_t (&d)[6], uint32_t a0, uint32_t a1, uint32_t a2, uint32_t a3, uint64_t dsc) {
  asm volatile("wgmma.mma_async.sync.aligned.m64n24k16.f16.f16.f16 {%0,%1,%2,%3,%4,%5}, {%6,%7,%8,%9}, %10, 1, 1, 1, 1;\n"
   : "+r"(d[0]),"+r"(d[1]),"+r"(d[2]),"+r"(d[3]),"+r"(d[4]),"+r"(d[5])
   : "r"(a0), "r"(a1), "r"(a2), "r"(a3), "l"(dsc));
}
__device__ __forceinline__ void mma_pv_z(uint32_t (&d)[6], uint32_t a0, uint32_t a1, uint32_t a2, uint32_t a3, uint64_t dsc) {
  asm volatile("wgmma.mma_async.sync.aligned.m64n24k16.f16.f16.f16 {%0,%1,%2,%3,%4,%5}, {%6,%7,%8,%9}, %10, 0, 1, 1, 1;\n"
   : "=r"(d[0]),"=r"(d[1]),"=r"(d[2]),"=r"(d[3]),"=r"(d[4]),"=r"(d[5])
   : "r"(a0), "r"(a1), "r"(a2), "r"(a3), "l"(dsc));
}

__device__ __forceinline__ uint32_t exp2_fma(uint32_t y, uint32_t c1, uint32_t c2) {
    uint32_t r = hfma2_relu(y, 0x00800080u, c1);
    uint32_t g = hfma2(r, 0xF800F800u, c2);
    uint32_t w = hfma2_relu(g, 0x44004400u, y);
    uint32_t s = hfma2(w, w, 0x080B080Bu);
    return s + __funnelshift_l(r, r, 10);
}
template <int U>
__device__ __forceinline__ void exp_stage(const uint32_t (&s)[16], uint32_t (&p)[16], uint32_t c1, uint32_t c2) {
#pragma unroll
    for (int i = 0; i < 16; i++) p[i] = grp_is_mufu(U * 8 + (i >> 1)) ? ex2_h2(s[i]) : exp2_fma(s[i], c1, c2);
}
template <bool Z>
__device__ __forceinline__ void pv_stage(uint32_t (&oh)[6], const uint32_t (&p)[16], uint64_t dv) {
    if (Z) mma_pv_z(oh, p[0], p[1], p[2], p[3], dv); else mma_pv(oh, p[0], p[1], p[2], p[3], dv);
    mma_pv(oh, p[4], p[5], p[6], p[7], dv + 16);
    mma_pv(oh, p[8], p[9], p[10], p[11], dv + 32);
    mma_pv(oh, p[12], p[13], p[14], p[15], dv + 48);
}

__device__ __noinline__ void attention_exact(const __nv_bfloat16* __restrict__ x, const __nv_bfloat16* __restrict__ wqkv, int h, int row0,
                                             int tid, int barid, const float* gate_s, bool write) {
    __nv_bfloat16* kv = g_fb + (size_t)h * kS * 32;
    for (int key = tid; key < kS; key += 128) {
        float acc[32];
#pragma unroll
        for (int i = 0; i < 32; i++) acc[i] = 0.f;
        for (int d = 0; d < kD; d++) {
            float xv = __bfloat162float(x[(size_t)key * kD + d]);
            const uint4* wk = reinterpret_cast<const uint4*>(wqkv + (size_t)d * 1536 + 512 + h * 16);
            const uint4* wv = reinterpret_cast<const uint4*>(wqkv + (size_t)d * 1536 + 1024 + h * 16);
            uint4 w[4] = {wk[0], wk[1], wv[0], wv[1]};
#pragma unroll
            for (int i = 0; i < 4; i++) {
                acc[i * 8 + 0] += xv * bf_lo(w[i].x); acc[i * 8 + 1] += xv * bf_hi(w[i].x);
                acc[i * 8 + 2] += xv * bf_lo(w[i].y); acc[i * 8 + 3] += xv * bf_hi(w[i].y);
                acc[i * 8 + 4] += xv * bf_lo(w[i].z); acc[i * 8 + 5] += xv * bf_hi(w[i].z);
                acc[i * 8 + 6] += xv * bf_lo(w[i].w); acc[i * 8 + 7] += xv * bf_hi(w[i].w);
            }
        }
        uint4* dst = reinterpret_cast<uint4*>(kv + (size_t)key * 32);
#pragma unroll
        for (int i = 0; i < 4; i++)
            __stcg(dst + i, make_uint4(pack_bf2(acc[i * 8], acc[i * 8 + 1]), pack_bf2(acc[i * 8 + 2], acc[i * 8 + 3]),
                                       pack_bf2(acc[i * 8 + 4], acc[i * 8 + 5]), pack_bf2(acc[i * 8 + 6], acc[i * 8 + 7])));
    }
    __threadfence();
    bar_sync(barid, 128);
    const int rl = tid >> 1, par = tid & 1, row = row0 + rl;
    float q[16];
#pragma unroll
    for (int i = 0; i < 16; i++) q[i] = 0.f;
    for (int d = 0; d < kD; d++) {
        float xv = __bfloat162float(x[(size_t)row * kD + d]);
#pragma unroll
        for (int i = 0; i < 16; i++) q[i] += xv * __bfloat162float(wqkv[(size_t)d * 1536 + h * 16 + i]);
    }
#pragma unroll
    for (int i = 0; i < 16; i++) q[i] = bf_round(q[i]);
    auto score = [&](int key) {
        const uint4* kp = reinterpret_cast<const uint4*>(kv + (size_t)key * 32);
        uint4 a = __ldcg(kp), b = __ldcg(kp + 1);
        float s = q[0] * bf_lo(a.x) + q[1] * bf_hi(a.x) + q[2] * bf_lo(a.y) + q[3] * bf_hi(a.y) + q[4] * bf_lo(a.z) + q[5] * bf_hi(a.z) +
                  q[6] * bf_lo(a.w) + q[7] * bf_hi(a.w) + q[8] * bf_lo(b.x) + q[9] * bf_hi(b.x) + q[10] * bf_lo(b.y) + q[11] * bf_hi(b.y) +
                  q[12] * bf_lo(b.z) + q[13] * bf_hi(b.z) + q[14] * bf_lo(b.w) + q[15] * bf_hi(b.w);
        return bf_round(s) * 0.25f;
    };
    float m = -INFINITY;
    for (int key = par; key < kS; key += 2) m = fmaxf(m, score(key));
    m = fmaxf(m, __shfl_xor_sync(0xffffffffu, m, 1));
    float l = 0.f;
    for (int key = par; key < kS; key += 2) l += __expf(score(key) - m);
    l += __shfl_xor_sync(0xffffffffu, l, 1);
    const float il = 1.f / l;
    float o[16];
#pragma unroll
    for (int i = 0; i < 16; i++) o[i] = 0.f;
    for (int key = par; key < kS; key += 2) {
        float p = bf_round(__expf(score(key) - m) * il);
        const uint4* vp = reinterpret_cast<const uint4*>(kv + (size_t)key * 32 + 16);
        uint4 a = __ldcg(vp), b = __ldcg(vp + 1);
        o[0] += p * bf_lo(a.x); o[1] += p * bf_hi(a.x); o[2] += p * bf_lo(a.y); o[3] += p * bf_hi(a.y);
        o[4] += p * bf_lo(a.z); o[5] += p * bf_hi(a.z); o[6] += p * bf_lo(a.w); o[7] += p * bf_hi(a.w);
        o[8] += p * bf_lo(b.x); o[9] += p * bf_hi(b.x); o[10] += p * bf_lo(b.y); o[11] += p * bf_hi(b.y);
        o[12] += p * bf_lo(b.z); o[13] += p * bf_hi(b.z); o[14] += p * bf_lo(b.w); o[15] += p * bf_hi(b.w);
    }
    const float gt = gate_s[rl];
#pragma unroll
    for (int i = 0; i < 16; i++) o[i] = (o[i] + __shfl_xor_sync(0xffffffffu, o[i], 1)) * gt;
    uint4 v = par ? make_uint4(pack_bf2(o[8], o[9]), pack_bf2(o[10], o[11]), pack_bf2(o[12], o[13]), pack_bf2(o[14], o[15]))
                  : make_uint4(pack_bf2(o[0], o[1]), pack_bf2(o[2], o[3]), pack_bf2(o[4], o[5]), pack_bf2(o[6], o[7]));
    if (h < 16) {
        g_O[((row >> 6) * 32 + h * 2 + par) * 64 + rl] = v;
    } else if (write) {
        uint32_t* p = reinterpret_cast<uint32_t*>(g_O1 + ((row >> 6) * 16 + h - 16) * 128 + (rl >> 4) * 32 + (rl & 7) * 4) + par * 2 + ((rl >> 3) & 1);
        st_relaxed(p, ~v.x); st_relaxed(p + 4, ~v.y); st_relaxed(p + 8, ~v.z); st_relaxed(p + 12, ~v.w);
    }
    bar_sync(barid, 128);
}

struct Params {
    const __nv_bfloat16 *x, *wqkv, *wo, *w1, *b1, *w2, *b2, *gw;
    __nv_bfloat16* out;
};

__device__ __forceinline__ void load_kv_chunk(uint32_t sb, int rank, int h, int c) {
    const uint4* src = g_KV + (h * 8 + c) * 1024;
    const uint32_t bar = sb + B_KVFULL + c * 8;
    e_expect(bar, 16384);
    if (c == 7) e_arrive(bar + 8);
    if (rank == 0) {
        e_bulk_mc(sb + c * 8192, src, 8192, bar);
    } else {
        e_bulk_mc(sb + 65536 + c * 4096, src + 512, 4096, bar);
        e_bulk_mc(sb + 98304 + c * 4096, src + 768, 4096, bar);
    }
}

__global__ void __cluster_dims__(2, 1, 1) __launch_bounds__(640, 1)
fused_kernel(const __grid_constant__ CUtensorMap tmX, const __grid_constant__ CUtensorMap tmWqkv, const __grid_constant__ CUtensorMap tmW1,
             const __grid_constant__ CUtensorMap tmW2, const __grid_constant__ CUtensorMap tmWo, const Params P) {
    extern __shared__ __align__(1024) uint8_t smem[];
    const uint32_t sb = (uint32_t)__cvta_generic_to_shared(smem);
    const int wg = __shfl_sync(0xffffffffu, threadIdx.x >> 7, 0);
    const int warp = __shfl_sync(0xffffffffu, (threadIdx.x >> 5) & 3, 0);
    const int lane = threadIdx.x & 31, tid = threadIdx.x & 127, g = lane >> 2, t = lane & 3;
    const int cta = blockIdx.x, j = cta >> 4, mi = cta & 15, rank = cta & 1;
    const int hh = mi >> 3, qb = mi & 7;
    const int u = j * 2 + hh, rb = qb * 4 + (u & 3), cb = u >> 2;
    if ((sb & 0xFFFFFFu) != SB0) __trap();
    TLS(0); if (wg < 4) TLC(8);

    if (wg == 4) {
        if (warp < 2) {
            e_init(sb + B_XFULL + warp * 8, 1);
            fence_async_smem();
            if (warp == 0) {
                e_expect(sb + B_XFULL + warp * 8, 16384);
                e_tma2d(sb + ((XREG >> (warp * 4)) & 7) * 16384, &tmX, warp * 64, mi * 128, sb + B_XFULL + warp * 8);
            }
        } else {
            asm volatile("prefetch.tensormap [%0];" ::"l"(warp == 2 ? &tmWqkv : &tmW1) : "memory");
        }
    } else {
        if (threadIdx.x == 32) { *reinterpret_cast<uint32_t*>(smem + SM_TICK) = 0u; *reinterpret_cast<uint4*>(smem + SM_ORDER) = make_uint4(0, 0, 0, 0); }
        if (j == 7 && threadIdx.x < 16) *reinterpret_cast<uint32_t*>(smem + SM_B1 + 288 + threadIdx.x * 4) = 0u;
        const int w = wg * 4 + warp;
        if (w >= 2) e_init(sb + SM_BAR + w * 8, (uint32_t)(bar_counts(0) >> (w * 4)) & 15);
        e_init(sb + SM_BAR + 128 + w * 8, (uint32_t)(bar_counts(1) >> (w * 4)) & 15);
        e_init(sb + SM_BAR + 256 + w * 8, (uint32_t)(bar_counts(2) >> (w * 4)) & 15);
        fence_async_smem();
    }
    asm volatile("fence.mbarrier_init.release.cluster;" ::: "memory");
    asm volatile("barrier.cluster.arrive.relaxed.aligned;" ::: "memory");
    asm volatile("barrier.cluster.wait.aligned;" ::: "memory");
    auto load_w = [&](int s) {
        const uint32_t bar = sb + B_WFULL + (s & 3) * 8, dst = sb + SM_RING + (s & 3) * SLOT + rank * 12288;
        e_expect(bar, SLOT);
        if (s < 8) {
#pragma unroll
            for (int p = 0; p < 3; p++) e_tma2d_mc(dst + p * 4096, &tmWqkv, p * 512 + rank * 256 + j * 32, s * 64, bar);
        } else {
#pragma unroll
            for (int p = 0; p < 3; p++) e_tma2d_mc(dst + p * 4096, &tmW1, (j * 2 + rank) * 88 + p * 32, (s - 8) * 64, bar);
        }
    };
    auto load_x = [&](int k) {
        e_expect(sb + B_XFULL + k * 8, k < 7 ? 16384 : 16384 + (j == 7 ? 288 : 352));
        e_tma2d(sb + ((XREG >> (k * 4)) & 7) * 16384, &tmX, k * 64, mi * 128, sb + B_XFULL + k * 8);
        if (k == 7) e_bulk(sb + SM_B1, P.b1 + j * 176, j == 7 ? 288 : 352, sb + B_XFULL + 56);
    };
    if (wg == 4 && warp == 0) {
        TLS(12);
        load_w(0);
        load_x(1);
        load_w(1); load_x(2); load_w(2); load_x(3); load_w(3);
        load_x(4);
        e_prefetch(reinterpret_cast<const uint8_t*>(P.wqkv) + 786432 + cta * 6144, 6144);
        TLS(13);
    }

    if (wg < 4) {
        const int mh = wg & 1, nh = wg >> 1;
        const int kg = mi * 16 + mh * 8 + warp * 2;
        uint32_t pk[24];
        {
            float acc[48];
#pragma unroll 1
            for (int s = 0; s < 8; s++) {
                const uint64_t da = mkdesc(SB0 + ((XREG >> (s * 4)) & 7) * 16384 + mh * 8192, 16, 1024, 1);
                const uint64_t db = mkdesc(SB0 + SM_RING + (s & 3) * SLOT + nh * 12288, 4096, 512, 2);
                mbar_wait(sb + B_XFULL + s * 8, 0);
                if (s == 0) TLS(11);
                mbar_wait(sb + B_WFULL + (s & 3) * 8, (s >> 2) & 1);
                if ((s & 1) == 0) TLS(12 + (s >> 1));
                wg_fence();
                mma_n96(acc, da, db, s);
                mma_n96(acc, da + 2, db + 64, 1);
                mma_n96(acc, da + 4, db + 128, 1);
                mma_n96(acc, da + 6, db + 192, 1);
                wg_commit();
                wg_wait<0>();
                if (tid < 2) mbar_arrive_rank(sb + B_WEMPTY + (s & 3) * 8, tid);
            }
            TLS(1); TLC(9);
            const float ks0 = grp_is_mufu(kg) ? 1.f : kLam, ks1 = grp_is_mufu(kg + 1) ? 1.f : kLam;
            const float vs0 = grp_is_mufu(kg) ? 1.f : kPScale, vs1 = grp_is_mufu(kg + 1) ? 1.f : kPScale;
#pragma unroll
            for (int i = 0; i < 8; i++) {
                pk[i] = pack_h2(acc[2 * i] * kQScale, acc[2 * i + 1] * kQScale);
                pk[8 + i] = pack_h2(acc[16 + 2 * i] * ((i & 1) ? ks1 : ks0), acc[17 + 2 * i] * ((i & 1) ? ks1 : ks0));
                pk[16 + i] = pack_h2(acc[32 + 2 * i] * ((i & 1) ? vs1 : vs0), acc[33 + 2 * i] * ((i & 1) ? vs1 : vs0));
            }
            TLS(2);
        }
        {
            float acc[44];
            auto stage = [&](int s) {
                const uint64_t da = mkdesc(SB0 + ((XREG >> (s * 4)) & 7) * 16384 + mh * 8192, 16, 1024, 1);
                const uint64_t db = mkdesc(SB0 + SM_RING + (s & 3) * SLOT + nh * 12288, 4096, 512, 2);
                mbar_wait(sb + B_WFULL + (s & 3) * 8, (s >> 2) & 1);
                wg_fence();
                mma_n88(acc, da, db, s);
                mma_n88(acc, da + 2, db + 64, 1);
                mma_n88(acc, da + 4, db + 128, 1);
                mma_n88(acc, da + 6, db + 192, 1);
                wg_commit();
            };
            const int r16 = mi * 8 + mh * 4 + warp;
            auto store_part = [&](int part) {
#pragma unroll
                for (int e = 0; e < 2; e++) {
                    const int h = j * 2 + e;
                    const uint32_t* q = pk + e * 4; const uint32_t* k = pk + 8 + e * 4; const uint32_t* v = pk + 16 + e * 4;
                    uint32_t* base = reinterpret_cast<uint32_t*>(g_KV + (h * 8 + (r16 >> 4)) * 1024) + lane;
                    if (part == 0) {
                        uint32_t* kb = base + ((r16 & 8) ? 3072 : 1024) + (r16 & 7) * 128;
                        kb[0] = k[0]; kb[32] = k[2]; kb[64] = k[1]; kb[96] = k[3];
                    } else if (part == 1) {
                        uint32_t* vb = base + (r16 & 15) * 64;
                        vb[0] = v[0]; vb[32] = v[1]; vb[2048] = v[2]; vb[2080] = v[3];
                    } else {
                        g_Q[(h * 128 + r16) * 32 + lane] = make_uint4(q[0], q[1], q[2], q[3]);
                    }
                }
            };
            uint32_t* nrm = reinterpret_cast<uint32_t*>(smem + SM_NST) + nh * 48 + mh * 4 + warp;
            auto norm_k = [&](int e) {
                const float ki0 = grp_is_mufu(kg) ? 1.f : 1.f / (kLam * kLam), ki1 = grp_is_mufu(kg + 1) ? 1.f : 1.f / (kLam * kLam);
                const uint32_t km = max_row_norm2(pk + 8 + e * 4, ki0, ki1);
                if (lane == 0) nrm[e * 24] = km;
            };
            auto norm_qv = [&](int e) {
                const uint32_t* v = pk + 16 + e * 4;
                const uint32_t qm = max_row_norm2(pk + e * 4, 1.f, 1.f);
                const uint32_t vm = __reduce_or_sync(0xffffffffu, (v[0] | v[1] | v[2] | v[3]) & 0x60006000u);
                if (lane < 2) nrm[e * 24 + 8 + lane * 8] = lane ? qm : vm;
            };
            auto release = [&](int s) { wg_wait<1>(); if (tid < 2) mbar_arrive_rank(sb + B_WEMPTY + (s & 3) * 8, s < 4 ? tid : rank); };
            auto release0 = [&](int s) { wg_wait<0>(); if (tid < 2) mbar_arrive_rank(sb + B_WEMPTY + (s & 3) * 8, s < 4 ? tid : rank); };
            stage(0); if (nh == 0) store_part(0); else norm_k(0);
            release0(0);
            stage(1); if (nh == 0) store_part(1); else norm_k(1);
            release0(1);
            stage(2); if (nh == 0) { store_part(2); bar_arrive(1, 288); }
            release0(2);
            stage(3); if (nh == 0) norm_k(0);
            release0(3);
            stage(4); if (nh == 0) norm_k(1);
            stage(5); release(4); if (j < 8) norm_qv(0);
            stage(6); release(5); if (j < 8) norm_qv(1);
            stage(7); release(6);
            wg_wait<0>();
            if (tid < 2) mbar_arrive_rank(sb + B_WEMPTY + 3 * 8, rank);
            TLS(3); TLC(10);
            uint32_t hp[22];
            const uint32_t* bias = reinterpret_cast<const uint32_t*>(smem + SM_B1) + nh * 44 + t;
#pragma unroll
            for (int b = 0; b < 11; b++) {
                hp[2 * b] = relu_sq(pack_bf2(acc[b * 4], acc[b * 4 + 1]), bias[b * 4]);
                hp[2 * b + 1] = relu_sq(pack_bf2(acc[b * 4 + 2], acc[b * 4 + 3]), bias[b * 4]);
            }
            mbar_wait(sb + B_WEMPTY + 2 * 8, 1);
            const uint32_t hb = sb + SM_RING + SLOT + wg * 11264 + warp * 256 + (lane >> 4) * 1024 + (lane & 15) * 16;
#pragma unroll
            for (int b = 0; b < 10; b += 2) stsm4(hb + b * 1024, hp[2 * b], hp[2 * b + 1], hp[2 * b + 2], hp[2 * b + 3]);
            asm volatile("stmatrix.sync.aligned.m8n8.x2.shared.b16 [%0], {%1, %2};" ::"r"(hb + 10240), "r"(hp[20]), "r"(hp[21]) : "memory");
            if (nh) {
                mbar_wait(sb + B_WEMPTY + 3 * 8, 1);
#pragma unroll
                for (int e = 0; e < 2; e++) {
                    uint8_t* sp = smem + SM_RING + 3 * SLOT + e * 12288;
                    const int r8 = mh * 4 + warp;
                    *reinterpret_cast<uint4*>(sp + r8 * 512 + lane * 16) = make_uint4(pk[e * 4], pk[e * 4 + 1], pk[e * 4 + 2], pk[e * 4 + 3]);
                    const uint32_t sa = sb + SM_RING + 3 * SLOT + e * 12288;
                    stsm4(sa + 4096 + r8 * 512 + lane * 16, pk[8 + e * 4], pk[10 + e * 4], pk[9 + e * 4], pk[11 + e * 4]);
                    stsm4(sa + 8192 + r8 * 256 + (lane >> 4) * 2048 + (lane & 15) * 16, pk[16 + e * 4], pk[17 + e * 4], pk[18 + e * 4], pk[19 + e * 4]);
                }
            }
            TLS(4);
        }
        mbar_wait(sb + B_AUX, 0);
        const uint32_t c1 = 0x00090009u + (cta >> 20), c2 = 0x253E253Eu + (cta >> 20);
#pragma unroll 1
        for (int r = 0; r < 2; r++) {
            const int h = r * 16 + j * 2 + hh;
            if (r) mbar_wait(sb + B_AUX1, 0);
            const uint4 qf = *reinterpret_cast<const uint4*>(smem + SM_Q + r * 8192 + (wg * 4 + warp) * 512 + lane * 16);
            uint32_t rel;
            asm("mapa.shared::cluster.u32 %0, %1, %2;" : "=r"(rel) : "r"(sb + B_KVEMPTY - 8), "r"(r ? rank : (tid & 1)));
            uint32_t s[16], pa[16], pb[16], oh[6], o2[6];
            constexpr uint64_t dka0 = mkdesc(SB0 + 4096, 128, 256, 0), dkb0 = mkdesc(SB0 + 98304, 128, 256, 0), dv0 = mkdesc(SB0, 128, 65536, 0);
            mbar_wait(sb + B_KVFULL, r);
            TLS(5 + r * 3); TLC(11 + r * 2);
            wg_fence();
            mma_qk64(s, qf.x, qf.y, qf.z, qf.w, dka0);
            wg_commit();
            if (r == 0) { fence_async_smem(); bar_arrive(2, 544); }
            wg_wait<0>();
#pragma unroll
            for (int i = 0; i < 6; i++) { oh[i] = 0; o2[i] = 0; }
#pragma unroll 1
            for (uint32_t c = 0; c < 8; c++) {
                const uint64_t dka = join64((uint32_t)dka0 + c * 512, (uint32_t)(dka0 >> 32)), dkb = join64((uint32_t)dkb0 + c * 256, (uint32_t)(dkb0 >> 32));
                const uint64_t dv = join64((uint32_t)dv0 + c * 512, (uint32_t)(dv0 >> 32) - c * 256);
                exp_stage<0>(s, pa, c1, c2);
                mbar_wait(sb + B_KVFULL + 8 + c * 8, r);
                wg_wait<0>();
#pragma unroll
                for (int i = 0; i < 6; i++) o2[i] = hadd2(o2[i], oh[i]);
                if (tid < 2) asm volatile("mbarrier.arrive.shared::cluster.b64 _, [%0];\nadd.u32 %0, %0, 8;" : "+r"(rel) :: "memory");
                wg_fence();
                mma_qk64(s, qf.x, qf.y, qf.z, qf.w, dka + 128); wg_commit();
                pv_stage<true>(oh, pa, dv); wg_commit();
                wg_wait<1>();

                exp_stage<1>(s, pb, c1, c2);
                wg_fence();
                mma_qk64(s, qf.x, qf.y, qf.z, qf.w, dkb); wg_commit();
                pv_stage<false>(oh, pb, dv + 64); wg_commit();
                wg_wait<1>();

                exp_stage<2>(s, pa, c1, c2);
                wg_fence();
                mma_qk64(s, qf.x, qf.y, qf.z, qf.w, dkb + 128); wg_commit();
                pv_stage<false>(oh, pa, dv + 128); wg_commit();
                wg_wait<1>();

                exp_stage<3>(s, pb, c1, c2);
                wg_fence();
                mma_qk64(s, qf.x, qf.y, qf.z, qf.w, dka + 512); wg_commit();
                pv_stage<false>(oh, pb, dv + 192); wg_commit();
                wg_wait<1>();
            }
            if (r == 0) mbar_wait(sb + B_GATE, 0);
            const float lmin = reinterpret_cast<const float*>(smem + SM_LMIN)[r * 16 + wg * 4 + warp];
            const float* gs = reinterpret_cast<const float*>(smem + SM_GATE) + wg * 64;
            const float g0 = gs[warp * 16 + g], g1 = gs[warp * 16 + g + 8];
            uint32_t* ob = reinterpret_cast<uint32_t*>(g_O + ((qb * 4 + wg) * 32 + u * 2) * 64) + warp * 64 + lane;
            uint4* ob1 = g_O1 + ((qb * 4 + wg) * 16 + u) * 128 + tid;
            wg_wait<0>();
            if (tid < 2) asm volatile("mbarrier.arrive.shared::cluster.b64 _, [%0];" ::"r"(rel) : "memory");
            TLS(6 + r * 3); TLC(12 + r * 2);
            uint32_t nanq = 0;
#pragma unroll
            for (int i = 0; i < 6; i++) { o2[i] = hadd2(o2[i], oh[i]); nanq = hfma2(o2[i], 0u, nanq); }
            const float l0 = h_lo(o2[4]), l1 = h_lo(o2[5]);
            const bool ok = (l0 >= lmin) && (l1 >= lmin) && ((nanq & 0x7C007C00u) == 0);
            const float s0 = g0 * rcp(l0), s1 = g1 * rcp(l1);
            const uint32_t f0 = pack_bf2(h_lo(o2[0]) * s0, h_hi(o2[0]) * s0), f1 = pack_bf2(h_lo(o2[1]) * s1, h_hi(o2[1]) * s1);
            const uint32_t f2 = pack_bf2(h_lo(o2[2]) * s0, h_hi(o2[2]) * s0), f3 = pack_bf2(h_lo(o2[3]) * s1, h_hi(o2[3]) * s1);
            const bool wok = __all_sync(0xffffffffu, ok);
            if (r == 0) {
                ob[0] = f0; ob[32] = f1; ob[256] = f2; ob[288] = f3;
                st_relaxed4(ob1, 0u, 0u, 0u, 0u);
            } else if (wok) {
                st_relaxed4(ob1, ~f0, ~f1, ~f2, ~f3);
            }
            if (bar_or(4 + wg, 128, !ok)) attention_exact(P.x, P.wqkv, h, qb * 256 + wg * 64, tid, 8 + wg, gs, !wok);
            if (r == 0 && warp == 0) e_arrive(sb + B_ODONE);
            TLS(7 + r * 3);
        }
        {
            mbar_wait(sb + B_TAILGO, 0);
            const uint4* src = g_O1 + (rb * 16 + wg * 4 + warp) * 128 + lane;
            uint4 v[4];
            TLW(0);
            for (int n = 0; n < 64; n++) {
                bool full = true;
#pragma unroll
                for (int i = 0; i < 4; i++) { v[i] = ld_relaxed4(src + i * 32); full = full && v[i].x && v[i].y && v[i].z && v[i].w; }
                if (__all_sync(0xffffffffu, full)) break;
                for (int m = 0; m < (1 << 18); m++) {
                    uint32_t w;
                    asm volatile("ld.relaxed.gpu.global.u32 %0, [%1];" : "=r"(w) : "l"(src - lane + (lane & 3) * 32 + 31) : "memory");
                    if (__all_sync(0xffffffffu, w != 0)) break;
                }
            }
            TLW(2);
            const uint32_t ta = sb + wg * 8192 + warp * 2048 + (lane >> 4) * 1024 + (lane & 15) * 16;
#pragma unroll
            for (int i = 0; i < 4; i++) stsm4(ta + i * 256, ~v[i].x, ~v[i].y, ~v[i].z, ~v[i].w);
            fence_async_smem();
            __syncwarp();
            TLW(3);
            if (lane == 0) {
                const unsigned slot = atomicAdd(reinterpret_cast<unsigned*>(smem + SM_TICK), 1u);
                asm volatile("st.release.cta.shared.u8 [%0], %1;" ::"r"(sb + SM_ORDER + slot), "r"(wg * 4 + warp + 1) : "memory");
            }
            TLW(15);
        }
    } else {
        unsigned epoch16 = 0;
        if (warp == 0) {
#pragma unroll 1
            for (int s = 4; s < 16; s++) {
                mbar_wait(sb + B_WEMPTY + (s & 3) * 8, ((s >> 2) - 1) & 1);
                TLW(s);
                load_w(s);
                if (s < 7) load_x(s + 1);
            }
            TLS(7);
            mbar_wait(sb + B_WEMPTY + 0 * 8, 1);
            bar_arrive(3, 96);
            e_expect(sb + B_AUX, 8192);
            mbar_wait(sb + B_FLAG, 0);
            fence_async_gmem();
            TLS(8);
            e_bulk(sb + SM_Q, g_Q + ((j * 2 + hh) * 128 + qb * 16) * 32, 8192, sb + B_AUX);
#pragma unroll
            for (int c = 0; c < 4; c++) load_kv_chunk(sb, rank, j * 2 + hh, c);
            epoch16 = *reinterpret_cast<volatile unsigned*>(smem + SM_EPOCH);
            TLS(9);
        } else if (warp == 1) {
            if (lane == 0) epoch16 = ((atomicAdd(g_cnt + CNT_TICKET * 32, 1u) >> 7) + 1) * 16;
            epoch16 = __shfl_sync(0xffffffffu, epoch16, 0);
            *reinterpret_cast<volatile unsigned*>(smem + SM_EPOCH) = epoch16;
            bar_sync(1, 288);
            TLW(0);
            e_signal(CNT_QKV + j);
            TLW(1);
            cnt_wait(CNT_QKV + j, epoch16);
            TLW(2);
            e_arrive(sb + B_FLAG);
        } else {
            mbar_wait(sb + B_XFULL + 4 * 8, 0);
            if (warp == 3) {
                e_prefetch(reinterpret_cast<const uint8_t*>(P.w1) + cta * 11008, 11008);
                e_prefetch(reinterpret_cast<const uint8_t*>(P.w2) + cta * 11008, 11008);
                e_prefetch(reinterpret_cast<const uint8_t*>(P.wo) + cta * 4096, 4096);
            }
            const uint4 wa = *reinterpret_cast<const uint4*>(P.gw + lane * 8), wb = *reinterpret_cast<const uint4*>(P.gw + 256 + lane * 8);
            const int row0 = mi * 128 + j * 16 + (warp - 2) * 8;
            float mine = 0.f;
#pragma unroll
            for (int i = 0; i < 8; i++) {
                const uint4 xa = *reinterpret_cast<const uint4*>(P.x + (size_t)(row0 + i) * kD + lane * 8);
                const uint4 xb = *reinterpret_cast<const uint4*>(P.x + (size_t)(row0 + i) * kD + 256 + lane * 8);
                float a = bf_lo(xa.x) * bf_lo(wa.x) + bf_hi(xa.x) * bf_hi(wa.x) + bf_lo(xa.y) * bf_lo(wa.y) + bf_hi(xa.y) * bf_hi(wa.y) +
                          bf_lo(xa.z) * bf_lo(wa.z) + bf_hi(xa.z) * bf_hi(wa.z) + bf_lo(xa.w) * bf_lo(wa.w) + bf_hi(xa.w) * bf_hi(wa.w) +
                          bf_lo(xb.x) * bf_lo(wb.x) + bf_hi(xb.x) * bf_hi(wb.x) + bf_lo(xb.y) * bf_lo(wb.y) + bf_hi(xb.y) * bf_hi(wb.y) +
                          bf_lo(xb.z) * bf_lo(wb.z) + bf_hi(xb.z) * bf_hi(wb.z) + bf_lo(xb.w) * bf_lo(wb.w) + bf_hi(xb.w) * bf_hi(wb.w);
#pragma unroll
                for (int o = 16; o > 0; o >>= 1) a += __shfl_xor_sync(0xffffffffu, a, o);
                if (lane == i) mine = a;
            }
            if (lane < 8) g_gate[row0 + lane] = 1.f / (1.f + __expf(-mine));
            __syncwarp();
            e_signal(CNT_H + mi * 2 + (j >> 2));
            bar_sync(3, 96);
#pragma unroll
            for (int i = 0; i < 4; i++) {
                const int key = (warp - 2) * 128 + i * 32 + lane;
                const uint32_t v = grp_is_mufu(key >> 3) ? 0x3C003C00u : kPScaleH2;
                *reinterpret_cast<uint4*>(smem + SM_ONES + key * 16) = make_uint4(v, v, v, v);
            }
            fence_async_smem();
            __syncwarp();
            e_arrive(sb + B_AUX);
        }
        const uint4* const hsrc = g_H + rb * 176 * 64;
        const uint4* const osrc = g_O + rb * 32 * 64;
        auto load_b = [&](const CUtensorMap* tm, int k, int sl) {
            e_expect(sb + B_FFULL + sl * 8, SLOT);
            e_tma3d(sb + SM_RING + (1 + sl) * SLOT + 8192, tm, 0, k * 64, cb * 2, sb + B_FFULL + sl * 8);
        };
        auto load_a = [&](const uint4* src, int sl) { e_bulk(sb + SM_RING + (1 + sl) * SLOT, src, 8192, sb + B_FFULL + sl * 8); };
        auto guard1 = [&]() {
            mbar_wait(sb + B_AUX1, 0);
#pragma unroll
            for (int r = 0; r < 2; r++) {
                const uint4 nk = *reinterpret_cast<const uint4*>(smem + SM_NRM + r * 1536 + lane * 16);
                const uint4 nv = *reinterpret_cast<const uint4*>(smem + SM_NRM + r * 1536 + 512 + lane * 16);
                const float km = __uint_as_float(__reduce_max_sync(0xffffffffu, max(max(nk.x, nk.y), max(nk.z, nk.w))));
                const uint32_t vm = __reduce_or_sync(0xffffffffu, nv.x | nv.y | nv.z | nv.w);
                const float qm = reinterpret_cast<const float*>(smem + SM_NRM + r * 1536 + 1024)[qb * 16 + (lane & 15)];
                const bool ok = (qm <= 4096.f) && (km <= 16777216.f) && (vm != 0) && (qm * km <= 334.f);
                if (lane < 16) reinterpret_cast<float*>(smem + SM_LMIN)[r * 16 + lane] = !ok ? INFINITY : qm * km <= 88.f ? 0.f : 1024.f;
            }
            __syncwarp();
            e_arrive(sb + B_GATE);
        };
        int kvnext = 0;
        auto service_kv = [&]() {
            if (kvnext < 8) {
                if (mbar_test(sb + B_KVEMPTY + kvnext * 8, 0)) { load_kv_chunk(sb, rank, 16 + j * 2 + hh, kvnext); kvnext++; }
            } else if (kvnext == 8) {
                if (mbar_test(sb + B_ODONE, 0)) { signal_n(CNT_O + qb * 4, 4, lane); kvnext++; }
            }
        };
        if (warp == 0) {
            TLS(10);
            mbar_wait(sb + B_WEMPTY + 3 * 8, 1);
            if (lane == 0) mbar_arrive_rank(sb + B_XDEAD, rank ^ 1);
            __syncwarp();
            mbar_wait(sb + B_XDEAD, 0);
#pragma unroll
            for (int c = 4; c < 8; c++) load_kv_chunk(sb, rank, j * 2 + hh, c);
            TLS(11);
            bar_sync(12, 64);
            load_b(&tmW2, 0, 0); load_b(&tmW2, 1, 1);
            cnt_wait(lane < 4 ? CNT_H + qb * 4 + lane : CNT_QKV + 8 + j, epoch16);
            fence_async_gmem();
            e_expect(sb + B_AUX1, 8192 + 3072);
            e_bulk(sb + SM_NRM, g_nrm + (j * 2 + hh) * 384, 1536, sb + B_AUX1);
            e_bulk(sb + SM_Q + 8192, g_Q + ((16 + j * 2 + hh) * 128 + qb * 16) * 32, 8192, sb + B_AUX1);
            e_bulk(sb + SM_NRM + 1536, g_nrm + (16 + j * 2 + hh) * 384, 1536, sb + B_AUX1);
            e_expect(sb + B_GATE, 1024 + 256);
            e_bulk(sb + SM_B1, P.b2 + cb * 128, 256, sb + B_GATE);
            e_bulk(sb + SM_GATE, g_gate + qb * 256, 1024, sb + B_GATE);
            load_a(hsrc, 0); load_a(hsrc + 512, 1);
        } else if (warp == 1) {
            bar_sync(2, 544);
            TLW(3);
#pragma unroll
            for (int w = 0; w < 4; w++) {
                const int unit = j * 2 + (w >> 1);
                e_bulk_store(g_H + ((mi * 2 + (w & 1)) * 176 + unit * 11) * 64, sb + SM_RING + SLOT + w * 11264, 11264);
            }
#pragma unroll
            for (int e = 0; e < 2; e++) {
                const int h = 16 + j * 2 + e;
                const uint32_t sp = sb + SM_RING + 3 * SLOT + e * 12288;
                uint4* kv = g_KV + (h * 8 + (mi >> 1)) * 1024;
                e_bulk_store(g_Q + (h * 128 + mi * 8) * 32, sp, 4096);
                e_bulk_store(kv + ((mi & 1) ? 768 : 256), sp + 4096, 4096);
                e_bulk_store(kv + (mi & 1) * 128, sp + 8192, 2048);
                e_bulk_store(kv + 512 + (mi & 1) * 128, sp + 10240, 2048);
            }
            if (lane < 24) {
                const int rw = lane >> 1, hd = rw / 3;
                *reinterpret_cast<uint4*>(g_nrm + (((hd >> 1) * 16 + j * 2 + (hd & 1)) * 3 + rw % 3) * 128 + mi * 8 + (lane & 1) * 4) = *reinterpret_cast<const uint4*>(smem + SM_NST + lane * 16);
            }
            __syncwarp();
            asm volatile("{\n.reg .pred e;\nelect.sync _|e, 0xffffffff;\n@e cp.async.bulk.commit_group;\n@e cp.async.bulk.wait_group.read 0;\n}" ::: "memory");
            __syncwarp();
            bar_arrive(12, 64);
            asm volatile("{\n.reg .pred e;\nelect.sync _|e, 0xffffffff;\n@e cp.async.bulk.wait_group 0;\n}" ::: "memory");
            __syncwarp();
            TLW(4);
            fence_async_gmem();
            if (lane < 3) asm volatile("fence.acq_rel.gpu;\nred.relaxed.gpu.global.add.u32 [%0], 1;" ::"l"(g_cnt + (lane < 2 ? CNT_H + mi * 2 + lane : CNT_QKV + 8 + j) * 32) : "memory");
            __syncwarp();
            TLW(5);
        }
        bar_sync(14, 128);
        fence_async_gmem();
        epoch16 = *reinterpret_cast<volatile unsigned*>(smem + SM_EPOCH);
        TLS(1);
        float acc[64];
#pragma unroll 1
        for (int st = 0; st < 24; st += 3) {
            const uint64_t da = mkdesc(SB0 + SM_RING + SLOT, 1024, 128, 0) + (st >> 5), db = da + (mkdesc(8192, 8192, 1024, 1) - mkdesc(0, 1024, 128, 0));
#pragma unroll
            for (int sl = 0; sl < 3; sl++) {
                mbar_wait(sb + B_FFULL + sl * 8, st & 1);
                wg_fence();
                mma_n128(acc, da + sl * (SLOT / 16), db + sl * (SLOT / 16), sl ? 1 : st);
                mma_n128(acc, da + sl * (SLOT / 16) + 128, db + sl * (SLOT / 16) + 128, 1);
                wg_commit();
                if (warp == sl) {
                    const int ns = st + sl + 2;
                    if (ns < 22) {
                        load_b(&tmW2, ns, (sl + 2) % 3); load_a(hsrc + ns * 512, (sl + 2) % 3);
                    } else {
                        load_b(&tmWo, ns - 22, (sl + 2) % 3);
                        cnt_wait(CNT_O + rb, epoch16);
                        fence_async_gmem();
                        load_a(osrc + (ns - 22) * 512, (sl + 2) % 3);
                    }
                } else if (warp == 3) {
                    if (sl == 1 && st == 0) guard1();
                    int n = (sl == 2 && st == 18) ? (1 << 26) : 1;
                    do service_kv(); while (--n > 0 && kvnext < 9);
                }
                wg_wait<0>();
                if (sl == 2 && st == 21) break;
                wg_fence();
                mma_n128(acc, da + sl * (SLOT / 16) + 256, db + sl * (SLOT / 16) + 256, 1);
                mma_n128(acc, da + sl * (SLOT / 16) + 384, db + sl * (SLOT / 16) + 384, 1);
                wg_commit();
                wg_wait<0>();
                if (sl == 0 && st == 21) {
                    mbar_wait(sb + B_GATE, 0);
                    const float* gs = reinterpret_cast<const float*>(smem + SM_GATE) + (u & 3) * 64 + warp * 16 + g;
                    const float w0 = 1.f - gs[0], w1 = 1.f - gs[8];
#pragma unroll
                    for (int b = 0; b < 16; b++) {
                        const uint32_t bb = *reinterpret_cast<const uint32_t*>(smem + SM_B1 + b * 16 + t * 4);
                        acc[b * 4] = (acc[b * 4] + bf_lo(bb)) * w0; acc[b * 4 + 1] = (acc[b * 4 + 1] + bf_hi(bb)) * w0;
                        acc[b * 4 + 2] = (acc[b * 4 + 2] + bf_lo(bb)) * w1; acc[b * 4 + 3] = (acc[b * 4 + 3] + bf_hi(bb)) * w1;
                    }
                    TLS(2);
                }
            }
        }
        bar_sync(14, 128);
        if (warp == 0) {
            mbar_wait(sb + B_KVEMPTY + 5 * 8, 1);
            e_expect(sb + B_TAILB, 65536);
#pragma unroll
            for (int i = 0; i < 4; i++) e_tma3d(sb + tailb_off(i), &tmWo, 0, 256 + i * 64, cb * 2, sb + B_TAILB);
        }
        mbar_wait(sb + B_FFULL, 0);
        mbar_wait(sb + B_FFULL + 8, 0);
        mbar_wait(sb + B_KVEMPTY + HT * 8, 1);
        {
            constexpr uint64_t da = mkdesc(SB0 + SM_RING + SLOT, 1024, 128, 0), db = mkdesc(SB0 + SM_RING + SLOT + 8192, 8192, 1024, 1);
            wg_fence();
#pragma unroll
            for (int k = 2; k < 12; k++) {
                const int o = ((k >> 2) + 2) % 3 * (SLOT / 16) + (k & 3) * 128;
                mma_n128(acc, da + o, db + o, 1);
            }
            wg_commit();
        }
        TLS(3);
        mbar_wait(sb + B_TAILB, 0);
#pragma unroll 1
        for (int i = 0; i < 4; i++) {
            unsigned list = 0;
#pragma unroll
            for (int k = 0; k < 4; k++) {
                for (int n = 0; n < (1 << 26) && ((list >> (k * 8)) & 255) == 0; n++) {
                    unsigned w;
                    asm volatile("ld.acquire.cta.shared.u32 %0, [%1];" : "=r"(w) : "r"(sb + SM_ORDER + i * 4) : "memory");
                    list = __shfl_sync(0xffffffffu, w, 0);
                }
                const unsigned id = (((list >> (k * 8)) & 255) - 1) & 15;
                if (i == 3 && k == 3) TLS(4);
                wg_fence();
                mma_n128(acc, mkdesc(SB0, 1024, 128, 0) + id * 128, mkdesc(SB0, 8192, 1024, 1) + (tailb_off(id >> 2) >> 4) + (id & 3) * 128, 1);
                wg_commit();
            }
        }
        wg_wait<0>();
        TLS(5);
        {
            const int row = ((lane >> 3) & 1) * 8 + (lane & 7);
            const uint32_t wb = 81920 + (warp >> 1) * 32768 + (warp & 1) * 4096;
#pragma unroll
            for (int b = 0; b < 16; b += 2)
                stsm4(sb + wb + row * 256 + (((b + (lane >> 4)) ^ (row & 7)) << 4), pack_bf2(acc[b * 4], acc[b * 4 + 1]), pack_bf2(acc[b * 4 + 2], acc[b * 4 + 3]),
                      pack_bf2(acc[b * 4 + 4], acc[b * 4 + 5]), pack_bf2(acc[b * 4 + 6], acc[b * 4 + 7]));
            __syncwarp();
            uint4* op = reinterpret_cast<uint4*>(P.out + (size_t)(rb * 64 + warp * 16 + (lane >> 4)) * kD + cb * 128) + (lane & 15);
#pragma unroll
            for (int i = 0; i < 8; i++) {
                const int rr = i * 2 + (lane >> 4);
                op[i * 128] = *reinterpret_cast<const uint4*>(smem + wb + rr * 256 + (((lane & 15) ^ (rr & 7)) << 4));
            }
        }
        TLS(6);
    }
    TLDUMP();
}

typedef CUresult (*EncodeFn)(CUtensorMap*, CUtensorMapDataType, cuuint32_t, void*, const cuuint64_t*, const cuuint64_t*, const cuuint32_t*,
                             const cuuint32_t*, CUtensorMapInterleave, CUtensorMapSwizzle, CUtensorMapL2promotion, CUtensorMapFloatOOBfill);

void make_map(EncodeFn fn, CUtensorMap* tm, const void* ptr, uint64_t cols, uint64_t rows, uint32_t bc, uint32_t br, CUtensorMapSwizzle sw) {
    cuuint64_t dims[2] = {cols, rows}, strides[1] = {cols * 2};
    cuuint32_t box[2] = {bc, br}, es[2] = {1, 1};
    fn(tm, CU_TENSOR_MAP_DATA_TYPE_BFLOAT16, 2, const_cast<void*>(ptr), dims, strides, box, es, CU_TENSOR_MAP_INTERLEAVE_NONE, sw,
       CU_TENSOR_MAP_L2_PROMOTION_L2_128B, CU_TENSOR_MAP_FLOAT_OOB_FILL_NONE);
}

void make_map3(EncodeFn fn, CUtensorMap* tm, const void* ptr, uint64_t rows) {
    cuuint64_t dims[3] = {64, rows, 8}, strides[2] = {1024, 128};
    cuuint32_t box[3] = {64, 64, 2}, es[3] = {1, 1, 1};
    fn(tm, CU_TENSOR_MAP_DATA_TYPE_BFLOAT16, 3, const_cast<void*>(ptr), dims, strides, box, es, CU_TENSOR_MAP_INTERLEAVE_NONE, CU_TENSOR_MAP_SWIZZLE_128B,
       CU_TENSOR_MAP_L2_PROMOTION_L2_128B, CU_TENSOR_MAP_FLOAT_OOB_FILL_NONE);
}

}

extern "C" void kernel_launch(void* const* d_in, const int* in_sizes, int n_in, void* d_out, int out_size) {
    (void)in_sizes; (void)n_in; (void)out_size;
    Params P;
    P.x = (const __nv_bfloat16*)d_in[0]; P.wqkv = (const __nv_bfloat16*)d_in[1]; P.wo = (const __nv_bfloat16*)d_in[2];
    P.w1 = (const __nv_bfloat16*)d_in[4]; P.b1 = (const __nv_bfloat16*)d_in[5]; P.w2 = (const __nv_bfloat16*)d_in[6];
    P.b2 = (const __nv_bfloat16*)d_in[7]; P.gw = (const __nv_bfloat16*)d_in[8];
    P.out = (__nv_bfloat16*)d_out;
    void* fp = nullptr;
    cudaDriverEntryPointQueryResult qr;
    cudaGetDriverEntryPoint("cuTensorMapEncodeTiled", &fp, cudaEnableDefault, &qr);
    EncodeFn fn = (EncodeFn)fp;
    CUtensorMap tmX, tmWqkv, tmW1, tmW2, tmWo;
    make_map(fn, &tmX, P.x, kD, kS, 64, 128, CU_TENSOR_MAP_SWIZZLE_128B);
    make_map(fn, &tmWqkv, P.wqkv, 1536, kD, 32, 64, CU_TENSOR_MAP_SWIZZLE_64B);
    make_map(fn, &tmW1, P.w1, kF, kD, 32, 64, CU_TENSOR_MAP_SWIZZLE_64B);
    make_map3(fn, &tmW2, P.w2, kF);
    make_map3(fn, &tmWo, P.wo, kD);
    cudaFuncSetAttribute(fused_kernel, cudaFuncAttributeMaxDynamicSharedMemorySize, SMEM_BYTES);
    fused_kernel<<<128, 640, SMEM_BYTES>>>(tmX, tmWqkv, tmW1, tmW2, tmWo, P);
}
```
